```python
import torch

def _softmax(x, axis=-1):
    return torch.softmax(x, dim=axis)
def _gelu(x):
    return torch.nn.functional.gelu(x, approximate="tanh")
def _silu(x):
    return torch.nn.functional.silu(x)
def _sigmoid(x):
    return torch.sigmoid(x)
def _layernorm(x, axis=-1, eps=1e-5):
    m = x.mean(dim=axis, keepdim=True)
    v = x.var(dim=axis, keepdim=True, unbiased=False)
    return (x - m) / torch.sqrt(v + eps)
def _scatter_add(tgt, idx, src, axis=0):
    return tgt.clone().index_add_(axis, idx, src)
def _segment_sum(src, seg, n):
    out = torch.zeros((n,) + src.shape[1:], dtype=src.dtype)
    return out.index_add_(0, seg, src)
def _pad(x, pw):
    flat = tuple(v for pair in reversed(pw) for v in pair)
    return torch.nn.functional.pad(x, flat)

kernel_name = 'interleave_layers__mha_block__glu_gated_glu__prompt'

def setup_inputs():

    _w = (lambda a: (lambda t: t.to(torch.bfloat16) if t.is_floating_point() else t)(torch.as_tensor(a)))
    def _A_setup():
        B, S, D, H = 1, 2048, 448, 16
        return {
            "x": _w((lambda *s: torch.randn(*s, dtype=torch.bfloat16) * 0.05)(B, S, D)),
            "wqkv": _w((lambda *s: torch.randn(*s, dtype=torch.bfloat16) * 0.05)(D, 3 * D)),
            "wo": _w((lambda *s: torch.randn(*s, dtype=torch.bfloat16) * 0.05)(D, D)),
        }
    _A_in = _A_setup()

    def _B_setup():
        B, S, D, F = 1, 2048, 448, 1792
        return {
            "x": _w((lambda *s: torch.randn(*s, dtype=torch.bfloat16) * 0.05)(B, S, D)),
            "w_gate": _w((lambda *s: torch.randn(*s, dtype=torch.bfloat16) * 0.05)(D, F)),
            "w_up": _w((lambda *s: torch.randn(*s, dtype=torch.bfloat16) * 0.05)(D, F)),
            "w_down": _w((lambda *s: torch.randn(*s, dtype=torch.bfloat16) * 0.05)(F, D)),
        }
    _B_in = _B_setup()

    return {
        "A_x": _A_in["x"],
        "A_wqkv": _A_in["wqkv"],
        "A_wo": _A_in["wo"],
        "B_x": _B_in["x"],
        "B_w_gate": _B_in["w_gate"],
        "B_w_up": _B_in["w_up"],
        "B_w_down": _B_in["w_down"],
    }

def reference(A_x, A_wqkv, A_wo, B_x, B_w_gate, B_w_up, B_w_down):
    def _A_ref(x, wqkv, wo):
        B, S, D = x.shape
        H = 16
        Dh = D // H
        qkv = (lambda x, *d: x.permute(*d))((x @ wqkv).reshape(B, S, 3, H, Dh), 2, 0, 3, 1, 4)
        q, k, v = qkv[0], qkv[1], qkv[2]
        scores = torch.einsum("bhqd,bhkd->bhqk", q, k) * (Dh ** -0.5)
        p = _softmax(scores, axis=-1)
        o = torch.einsum("bhqk,bhkd->bhqd", p, v)
        return (lambda x, *d: x.permute(*d))(o, 0, 2, 1, 3).reshape(B, S, D) @ wo

    def _B_ref(x, w_gate, w_up, w_down):
        g = torch.einsum("bsd,df->bsf", x, w_gate)
        u = torch.einsum("bsd,df->bsf", x, w_up)
        h = _sigmoid(g) * u
        return torch.einsum("bsf,fd->bsd", h, w_down)

    x = A_x
    x = x + _A_ref(_layernorm(x, axis=-1), A_wqkv, A_wo)
    x = x + _B_ref(_layernorm(x, axis=-1), B_w_gate, B_w_up, B_w_down)
    x = x + _A_ref(_layernorm(x, axis=-1), A_wqkv, A_wo)
    x = x + _B_ref(_layernorm(x, axis=-1), B_w_gate, B_w_up, B_w_down)
    return x
```

```cpp
#include <cuda_runtime.h>
#include <cuda_bf16.h>
#include <cuda.h>
#include <stdint.h>

#define SEQ 2048
#define DM 448
#define FF 1792
#define NCTA 132
#define NTHREADS 640

#define SLOT 16384
#define NXS 7
#define NWS 6
#define SM_X 0
#define SM_W (NXS * SLOT)
#define SM_STG ((NXS + NWS) * SLOT)
#define SM_MISC (SM_STG + SLOT)
#define SM_BAR SM_MISC
#define SM_STATS (SM_MISC + 512)
#define SM_CSQ (SM_STATS + 1024)
#define SM_DEC (SM_CSQ + 704)
#define SM_TOTAL (SM_DEC + 64)
#define B_XF 0
#define B_XE 7
#define B_WF 14
#define B_WE 20
#define B_QF 26
#define B_STG 27
#define B_ST 29
#define NB_WG 1
#define NB_ORD0 5
#define NB_ORD1 6
#define NB_ALL 7
#define NB_STAT 8
#define NB_PST 10
#define NB_SKIP 9

__device__ __align__(1024) __nv_bfloat16 g_q[2 * 16 * SEQ * 32];
__device__ __align__(1024) __nv_bfloat16 g_kv[2 * 16 * 16 * 2 * 128 * 32];
__device__ __align__(1024) __nv_bfloat16 g_o[2 * SEQ * 512];
__device__ __align__(1024) __nv_bfloat16 g_x[3 * SEQ * DM];
__device__ __align__(1024) __nv_bfloat16 g_h[2 * SEQ * FF];
__device__ __align__(128) float2 g_st[3 * SEQ * 8];
__device__ __align__(128) float2 g_st0[SEQ];
__device__ __align__(128) float g_csp[16 * 1344];
__device__ __align__(128) float g_csgu[2 * FF];
__device__ __align__(128) float g_nrm[2 * 32 * 16 * 4];
#define FL_QKV 0
#define FL_O (FL_QKV + 256)
#define FL_X (FL_O + 32)
#define FL_H (FL_X + 384)
#define FL_ST0 (FL_H + 1024)
#define FL_CSQ (FL_ST0 + 16)
#define FL_CSGU (FL_CSQ + 8)
#define FL_N (FL_CSGU + 1)
__device__ __align__(128) unsigned g_flags[FL_N * 8];
__device__ unsigned g_epoch;
__device__ unsigned g_done;
#define TS(id) do {} while (0)

struct Params {
    CUtensorMap x_in;
    CUtensorMap x_ld;
    CUtensorMap x_st;
    CUtensorMap out_st;
    CUtensorMap h_ld;
    CUtensorMap h_st;
    CUtensorMap o_ld;
    CUtensorMap o_st;
    CUtensorMap wqkv;
    CUtensorMap wo;
    CUtensorMap wg;
    CUtensorMap wu;
    CUtensorMap wd;
    const __nv_bfloat16* x;
    const __nv_bfloat16* p_wqkv;
    const __nv_bfloat16* p_wo;
    const __nv_bfloat16* p_wg;
    const __nv_bfloat16* p_wu;
    const __nv_bfloat16* p_wd;
    int use_smid;
};

__device__ __forceinline__ long long globaltimer() { long long t; asm volatile("mov.u64 %0, %%globaltimer;" : "=l"(t)); return t; }
__device__ __forceinline__ uint32_t s2u(const void* p) { return (uint32_t)__cvta_generic_to_shared(p); }
__device__ __forceinline__ uint64_t mkdesc(uint32_t addr, uint32_t lbo, uint32_t sbo, uint32_t swz) {
    return (uint64_t)((addr & 0x3FFFF) >> 4) | ((uint64_t)(lbo >> 4) << 16) | ((uint64_t)(sbo >> 4) << 32) | ((uint64_t)swz << 62);
}
__device__ __forceinline__ void mbar_init(uint32_t b, int c) { asm volatile("mbarrier.init.shared::cta.b64 [%0], %1;" ::"r"(b), "r"(c)); }
__device__ __forceinline__ void mbar_expect(uint32_t b, uint32_t bytes) { asm volatile("mbarrier.arrive.expect_tx.shared::cta.b64 _, [%0], %1;" ::"r"(b), "r"(bytes) : "memory"); }
__device__ __forceinline__ void mbar_arrive(uint32_t b, uint32_t cnt) { asm volatile("mbarrier.arrive.shared::cta.b64 _, [%0], %1;" ::"r"(b), "r"(cnt) : "memory"); }
__device__ __forceinline__ void mbar_wait(uint32_t b, uint32_t ph) {
    asm volatile(
        "{\n.reg .pred p;\n.reg .u32 n;\nmov.u32 n, 0;\n"
        "LW:\nmbarrier.try_wait.parity.shared::cta.b64 p, [%0], %1;\n@p bra LD;\n"
        "add.u32 n, n, 1;\nsetp.lt.u32 p, n, 4000000;\n@p bra LW;\ntrap;\nLD:\n}" ::"r"(b), "r"(ph) : "memory");
}
__device__ __forceinline__ void nb_sync(int id, int n) { asm volatile("bar.sync %0, %1;" ::"r"(id), "r"(n) : "memory"); }
__device__ __forceinline__ void nb_arrive(int id, int n) { asm volatile("bar.arrive %0, %1;" ::"r"(id), "r"(n) : "memory"); }
__device__ __forceinline__ void wg_fence() { asm volatile("wgmma.fence.sync.aligned;" ::: "memory"); }
__device__ __forceinline__ void wg_commit() { asm volatile("wgmma.commit_group.sync.aligned;" ::: "memory"); }
template <int N> __device__ __forceinline__ void wg_wait() { asm volatile("wgmma.wait_group.sync.aligned %0;" ::"n"(N) : "memory"); }
template <int N> __device__ __forceinline__ void fence_regs(float (&d)[N]) {
#pragma unroll
    for (int i = 0; i < N; i++) asm volatile("" : "+f"(d[i])::"memory");
}
template <int N> __device__ __forceinline__ void zero_regs(float (&d)[N]) {
#pragma unroll
    for (int i = 0; i < N; i++) d[i] = 0.f;
    fence_regs(d);
}
template <int N> __device__ __forceinline__ void fence_regs(uint32_t (&d)[N]) {
#pragma unroll
    for (int i = 0; i < N; i++) asm volatile("" : "+r"(d[i])::"memory");
}
__device__ __forceinline__ void fence_async_smem() { asm volatile("fence.proxy.async.shared::cta;" ::: "memory"); }
__device__ __forceinline__ void fence_async_global() { asm volatile("fence.proxy.async.global;" ::: "memory"); }
__device__ __forceinline__ void tma_ld2(uint32_t dst, const CUtensorMap* tm, int c0, int c1, uint32_t bar) {
    asm volatile("cp.async.bulk.tensor.2d.shared::cluster.global.mbarrier::complete_tx::bytes [%0], [%1, {%3, %4}], [%2];"
                 ::"r"(dst), "l"(tm), "r"(bar), "r"(c0), "r"(c1) : "memory");
}
__device__ __forceinline__ void tma_ld3(uint32_t dst, const CUtensorMap* tm, int c0, int c1, int c2, uint32_t bar) {
    asm volatile("cp.async.bulk.tensor.3d.shared::cluster.global.mbarrier::complete_tx::bytes [%0], [%1, {%3, %4, %5}], [%2];"
                 ::"r"(dst), "l"(tm), "r"(bar), "r"(c0), "r"(c1), "r"(c2) : "memory");
}
__device__ __forceinline__ void tma_st2(const CUtensorMap* tm, int c0, int c1, uint32_t src) {
    asm volatile("cp.async.bulk.tensor.2d.global.shared::cta.bulk_group [%0, {%1, %2}], [%3];" ::"l"(tm), "r"(c0), "r"(c1), "r"(src) : "memory");
}
__device__ __forceinline__ void bulk_ld(uint32_t dst, const void* src, uint32_t bytes, uint32_t bar) {
    asm volatile("cp.async.bulk.shared::cluster.global.mbarrier::complete_tx::bytes [%0], [%1], %2, [%3];" ::"r"(dst), "l"(src), "r"(bytes), "r"(bar) : "memory");
}
__device__ __forceinline__ void bulk_st(void* dst, uint32_t src, uint32_t bytes) {
    asm volatile("cp.async.bulk.global.shared::cta.bulk_group [%0], [%1], %2;" ::"l"(dst), "r"(src), "r"(bytes) : "memory");
}
__device__ __forceinline__ void bulk_commit() { asm volatile("cp.async.bulk.commit_group;" ::: "memory"); }
__device__ __forceinline__ void bulk_wait_all() { asm volatile("cp.async.bulk.wait_group 0;" ::: "memory"); }
__device__ __forceinline__ void flag_release(int idx) {
    fence_async_global();
    asm volatile("red.release.gpu.global.add.u32 [%0], 1;" ::"l"(&g_flags[idx * 8]) : "memory");
}
__device__ __forceinline__ unsigned flag_ld(int idx) {
    unsigned v;
    asm volatile("ld.relaxed.gpu.global.u32 %0, [%1];" : "=r"(v) : "l"(&g_flags[idx * 8]) : "memory");
    return v;
}
__device__ __forceinline__ void fence_acq() { asm volatile("fence.acq_rel.gpu;" ::: "memory"); }
__device__ __forceinline__ void flag_wait(int idx, unsigned target) {
    unsigned n = 0;
    while ((int)(flag_ld(idx) - target) < 0) { if (++n > 4000000u) __trap(); }
    fence_acq();
}
__device__ __forceinline__ float ex2(float x) { float y; asm("ex2.approx.ftz.f32 %0, %1;" : "=f"(y) : "f"(x)); return y; }
__device__ __forceinline__ float rcp(float x) { float y; asm("rcp.approx.ftz.f32 %0, %1;" : "=f"(y) : "f"(x)); return y; }
__device__ __forceinline__ uint32_t packbf(float lo, float hi) { uint32_t y; asm("cvt.rn.bf16x2.f32 %0, %1, %2;" : "=r"(y) : "f"(hi), "f"(lo)); return y; }
__device__ __forceinline__ float bflo(uint32_t v) { return __uint_as_float(v << 16); }
__device__ __forceinline__ float bfhi(uint32_t v) { return __uint_as_float(v & 0xFFFF0000u); }
__device__ __forceinline__ void sts32(uint32_t a, uint32_t v) { asm volatile("st.shared.b32 [%0], %1;" ::"r"(a), "r"(v) : "memory"); }
__device__ __forceinline__ void stsm4(uint32_t a, uint32_t r0, uint32_t r1, uint32_t r2, uint32_t r3) {
    asm volatile("stmatrix.sync.aligned.m8n8.x4.shared.b16 [%0], {%1,%2,%3,%4};" ::"r"(a), "r"(r0), "r"(r1), "r"(r2), "r"(r3) : "memory");
}
__device__ __forceinline__ void ldsm4(uint32_t a, uint32_t& r0, uint32_t& r1, uint32_t& r2, uint32_t& r3) {
    asm volatile("ldmatrix.sync.aligned.m8n8.x4.shared.b16 {%0,%1,%2,%3}, [%4];" : "=r"(r0), "=r"(r1), "=r"(r2), "=r"(r3) : "r"(a) : "memory");
}

template <int TB> __device__ __forceinline__ void wgmma_rs_32(float (&d)[16], uint32_t a0, uint32_t a1, uint32_t a2, uint32_t a3, uint64_t db) {
    asm volatile("wgmma.mma_async.sync.aligned.m64n32k16.f32.bf16.bf16 {%0,%1,%2,%3,%4,%5,%6,%7,%8,%9,%10,%11,%12,%13,%14,%15}, {%16,%17,%18,%19}, %20, 1, 1, 1, %21;\n"
        : "+f"(d[0]), "+f"(d[1]), "+f"(d[2]), "+f"(d[3]), "+f"(d[4]), "+f"(d[5]), "+f"(d[6]), "+f"(d[7]),
        "+f"(d[8]), "+f"(d[9]), "+f"(d[10]), "+f"(d[11]), "+f"(d[12]), "+f"(d[13]), "+f"(d[14]), "+f"(d[15])
        : "r"(a0), "r"(a1), "r"(a2), "r"(a3), "l"(db), "n"(TB));
}
template <int TB> __device__ __forceinline__ void wgmma_ss_64(float (&d)[32], uint64_t da, uint64_t db) {
    asm volatile("wgmma.mma_async.sync.aligned.m64n64k16.f32.bf16.bf16 {%0,%1,%2,%3,%4,%5,%6,%7,%8,%9,%10,%11,%12,%13,%14,%15,%16,%17,%18,%19,%20,%21,%22,%23,%24,%25,%26,%27,%28,%29,%30,%31}, %32, %33, 1, 1, 1, 0, %34;\n"
        : "+f"(d[0]), "+f"(d[1]), "+f"(d[2]), "+f"(d[3]), "+f"(d[4]), "+f"(d[5]), "+f"(d[6]), "+f"(d[7]),
        "+f"(d[8]), "+f"(d[9]), "+f"(d[10]), "+f"(d[11]), "+f"(d[12]), "+f"(d[13]), "+f"(d[14]), "+f"(d[15]),
        "+f"(d[16]), "+f"(d[17]), "+f"(d[18]), "+f"(d[19]), "+f"(d[20]), "+f"(d[21]), "+f"(d[22]), "+f"(d[23]),
        "+f"(d[24]), "+f"(d[25]), "+f"(d[26]), "+f"(d[27]), "+f"(d[28]), "+f"(d[29]), "+f"(d[30]), "+f"(d[31])
        : "l"(da), "l"(db), "n"(TB));
}
template <int TB> __device__ __forceinline__ void wgmma_ssz_64(float (&d)[32], uint64_t da, uint64_t db) {
    asm volatile("wgmma.mma_async.sync.aligned.m64n64k16.f32.bf16.bf16 {%0,%1,%2,%3,%4,%5,%6,%7,%8,%9,%10,%11,%12,%13,%14,%15,%16,%17,%18,%19,%20,%21,%22,%23,%24,%25,%26,%27,%28,%29,%30,%31}, %32, %33, 0, 1, 1, 0, %34;\n"
        : "=f"(d[0]), "=f"(d[1]), "=f"(d[2]), "=f"(d[3]), "=f"(d[4]), "=f"(d[5]), "=f"(d[6]), "=f"(d[7]),
        "=f"(d[8]), "=f"(d[9]), "=f"(d[10]), "=f"(d[11]), "=f"(d[12]), "=f"(d[13]), "=f"(d[14]), "=f"(d[15]),
        "=f"(d[16]), "=f"(d[17]), "=f"(d[18]), "=f"(d[19]), "=f"(d[20]), "=f"(d[21]), "=f"(d[22]), "=f"(d[23]),
        "=f"(d[24]), "=f"(d[25]), "=f"(d[26]), "=f"(d[27]), "=f"(d[28]), "=f"(d[29]), "=f"(d[30]), "=f"(d[31])
        : "l"(da), "l"(db), "n"(TB));
}
template <int TB> __device__ __forceinline__ void wgmma_rs_64(float (&d)[32], uint32_t a0, uint32_t a1, uint32_t a2, uint32_t a3, uint64_t db) {
    asm volatile("wgmma.mma_async.sync.aligned.m64n64k16.f32.bf16.bf16 {%0,%1,%2,%3,%4,%5,%6,%7,%8,%9,%10,%11,%12,%13,%14,%15,%16,%17,%18,%19,%20,%21,%22,%23,%24,%25,%26,%27,%28,%29,%30,%31}, {%32,%33,%34,%35}, %36, 1, 1, 1, %37;\n"
        : "+f"(d[0]), "+f"(d[1]), "+f"(d[2]), "+f"(d[3]), "+f"(d[4]), "+f"(d[5]), "+f"(d[6]), "+f"(d[7]),
        "+f"(d[8]), "+f"(d[9]), "+f"(d[10]), "+f"(d[11]), "+f"(d[12]), "+f"(d[13]), "+f"(d[14]), "+f"(d[15]),
        "+f"(d[16]), "+f"(d[17]), "+f"(d[18]), "+f"(d[19]), "+f"(d[20]), "+f"(d[21]), "+f"(d[22]), "+f"(d[23]),
        "+f"(d[24]), "+f"(d[25]), "+f"(d[26]), "+f"(d[27]), "+f"(d[28]), "+f"(d[29]), "+f"(d[30]), "+f"(d[31])
        : "r"(a0), "r"(a1), "r"(a2), "r"(a3), "l"(db), "n"(TB));
}
template <int TB> __device__ __forceinline__ void wgmma_rsz_64(float (&d)[32], uint32_t a0, uint32_t a1, uint32_t a2, uint32_t a3, uint64_t db) {
    asm volatile("wgmma.mma_async.sync.aligned.m64n64k16.f32.bf16.bf16 {%0,%1,%2,%3,%4,%5,%6,%7,%8,%9,%10,%11,%12,%13,%14,%15,%16,%17,%18,%19,%20,%21,%22,%23,%24,%25,%26,%27,%28,%29,%30,%31}, {%32,%33,%34,%35}, %36, 0, 1, 1, %37;\n"
        : "=f"(d[0]), "=f"(d[1]), "=f"(d[2]), "=f"(d[3]), "=f"(d[4]), "=f"(d[5]), "=f"(d[6]), "=f"(d[7]),
        "=f"(d[8]), "=f"(d[9]), "=f"(d[10]), "=f"(d[11]), "=f"(d[12]), "=f"(d[13]), "=f"(d[14]), "=f"(d[15]),
        "=f"(d[16]), "=f"(d[17]), "=f"(d[18]), "=f"(d[19]), "=f"(d[20]), "=f"(d[21]), "=f"(d[22]), "=f"(d[23]),
        "=f"(d[24]), "=f"(d[25]), "=f"(d[26]), "=f"(d[27]), "=f"(d[28]), "=f"(d[29]), "=f"(d[30]), "=f"(d[31])
        : "r"(a0), "r"(a1), "r"(a2), "r"(a3), "l"(db), "n"(TB));
}
template <int TB> __device__ __forceinline__ void wgmma_ss_128(float (&d)[64], uint64_t da, uint64_t db) {
    asm volatile("wgmma.mma_async.sync.aligned.m64n128k16.f32.bf16.bf16 {%0,%1,%2,%3,%4,%5,%6,%7,%8,%9,%10,%11,%12,%13,%14,%15,%16,%17,%18,%19,%20,%21,%22,%23,%24,%25,%26,%27,%28,%29,%30,%31,%32,%33,%34,%35,%36,%37,%38,%39,%40,%41,%42,%43,%44,%45,%46,%47,%48,%49,%50,%51,%52,%53,%54,%55,%56,%57,%58,%59,%60,%61,%62,%63}, %64, %65, 1, 1, 1, 0, %66;\n"
        : "+f"(d[0]), "+f"(d[1]), "+f"(d[2]), "+f"(d[3]), "+f"(d[4]), "+f"(d[5]), "+f"(d[6]), "+f"(d[7]),
        "+f"(d[8]), "+f"(d[9]), "+f"(d[10]), "+f"(d[11]), "+f"(d[12]), "+f"(d[13]), "+f"(d[14]), "+f"(d[15]),
        "+f"(d[16]), "+f"(d[17]), "+f"(d[18]), "+f"(d[19]), "+f"(d[20]), "+f"(d[21]), "+f"(d[22]), "+f"(d[23]),
        "+f"(d[24]), "+f"(d[25]), "+f"(d[26]), "+f"(d[27]), "+f"(d[28]), "+f"(d[29]), "+f"(d[30]), "+f"(d[31]),
        "+f"(d[32]), "+f"(d[33]), "+f"(d[34]), "+f"(d[35]), "+f"(d[36]), "+f"(d[37]), "+f"(d[38]), "+f"(d[39]),
        "+f"(d[40]), "+f"(d[41]), "+f"(d[42]), "+f"(d[43]), "+f"(d[44]), "+f"(d[45]), "+f"(d[46]), "+f"(d[47]),
        "+f"(d[48]), "+f"(d[49]), "+f"(d[50]), "+f"(d[51]), "+f"(d[52]), "+f"(d[53]), "+f"(d[54]), "+f"(d[55]),
        "+f"(d[56]), "+f"(d[57]), "+f"(d[58]), "+f"(d[59]), "+f"(d[60]), "+f"(d[61]), "+f"(d[62]), "+f"(d[63])
        : "l"(da), "l"(db), "n"(TB));
}
template <int TB> __device__ __forceinline__ void wgmma_ss_112(float (&d)[56], uint64_t da, uint64_t db) {
    asm volatile("wgmma.mma_async.sync.aligned.m64n112k16.f32.bf16.bf16 {%0,%1,%2,%3,%4,%5,%6,%7,%8,%9,%10,%11,%12,%13,%14,%15,%16,%17,%18,%19,%20,%21,%22,%23,%24,%25,%26,%27,%28,%29,%30,%31,%32,%33,%34,%35,%36,%37,%38,%39,%40,%41,%42,%43,%44,%45,%46,%47,%48,%49,%50,%51,%52,%53,%54,%55}, %56, %57, 1, 1, 1, 0, %58;\n"
        : "+f"(d[0]), "+f"(d[1]), "+f"(d[2]), "+f"(d[3]), "+f"(d[4]), "+f"(d[5]), "+f"(d[6]), "+f"(d[7]),
        "+f"(d[8]), "+f"(d[9]), "+f"(d[10]), "+f"(d[11]), "+f"(d[12]), "+f"(d[13]), "+f"(d[14]), "+f"(d[15]),
        "+f"(d[16]), "+f"(d[17]), "+f"(d[18]), "+f"(d[19]), "+f"(d[20]), "+f"(d[21]), "+f"(d[22]), "+f"(d[23]),
        "+f"(d[24]), "+f"(d[25]), "+f"(d[26]), "+f"(d[27]), "+f"(d[28]), "+f"(d[29]), "+f"(d[30]), "+f"(d[31]),
        "+f"(d[32]), "+f"(d[33]), "+f"(d[34]), "+f"(d[35]), "+f"(d[36]), "+f"(d[37]), "+f"(d[38]), "+f"(d[39]),
        "+f"(d[40]), "+f"(d[41]), "+f"(d[42]), "+f"(d[43]), "+f"(d[44]), "+f"(d[45]), "+f"(d[46]), "+f"(d[47]),
        "+f"(d[48]), "+f"(d[49]), "+f"(d[50]), "+f"(d[51]), "+f"(d[52]), "+f"(d[53]), "+f"(d[54]), "+f"(d[55])
        : "l"(da), "l"(db), "n"(TB));
}
template <int TB> __device__ __forceinline__ void wgmma_ss_56(float (&d)[28], uint64_t da, uint64_t db) {
    asm volatile("wgmma.mma_async.sync.aligned.m64n56k16.f32.bf16.bf16 {%0,%1,%2,%3,%4,%5,%6,%7,%8,%9,%10,%11,%12,%13,%14,%15,%16,%17,%18,%19,%20,%21,%22,%23,%24,%25,%26,%27}, %28, %29, 1, 1, 1, 0, %30;\n"
        : "+f"(d[0]), "+f"(d[1]), "+f"(d[2]), "+f"(d[3]), "+f"(d[4]), "+f"(d[5]), "+f"(d[6]), "+f"(d[7]),
        "+f"(d[8]), "+f"(d[9]), "+f"(d[10]), "+f"(d[11]), "+f"(d[12]), "+f"(d[13]), "+f"(d[14]), "+f"(d[15]),
        "+f"(d[16]), "+f"(d[17]), "+f"(d[18]), "+f"(d[19]), "+f"(d[20]), "+f"(d[21]), "+f"(d[22]), "+f"(d[23]),
        "+f"(d[24]), "+f"(d[25]), "+f"(d[26]), "+f"(d[27])
        : "l"(da), "l"(db), "n"(TB));
}

struct Ring {
    uint32_t slot, mask;
    template <int NS> __device__ __forceinline__ void adv() { mask ^= 1u << slot; slot = (slot + 1 == NS) ? 0 : slot + 1; }
    template <int NS> __device__ __forceinline__ void skip(const int n) {
        const uint32_t all = (1u << NS) - 1, bits = ((1u << (n % NS)) - 1) << slot;
        mask ^= ((bits | (bits >> NS)) & all) ^ (((n / NS) & 1) ? all : 0u);
        slot += n % NS;
        slot = slot >= NS ? slot - NS : slot;
    }
    __device__ __forceinline__ uint32_t par() const { return (mask >> slot) & 1u; }
    __device__ __forceinline__ void uniform() { slot = __shfl_sync(0xffffffffu, slot, 0); mask = __shfl_sync(0xffffffffu, mask, 0); }
};
__device__ __forceinline__ uint32_t wrap7(uint32_t s) { return s >= NXS ? s - NXS : s; }

#define K_MUFU_BITS 0x4000u
#define K_POLY_BITS 0x4398u
#define ONE_BITS 0x3F80u
#define SAFE_BOUND2 (44.0f * 44.0f)

__device__ __forceinline__ uint32_t exp2_pair(float t0, float t1, uint32_t cneg1) {
    uint32_t w = __byte_perm(__float_as_uint(t0), __float_as_uint(t1), 0x6521);
    uint32_t u, y, z, r;
    asm("lop3.b32 %0, %1, 0x007F007F, %2, 0xEA;" : "=r"(u) : "r"(w), "r"(cneg1));
    asm("fma.rn.f16x2 %0, %1, %2, %3;" : "=r"(y) : "r"(u), "r"(0xC72CC72Cu), "r"(0xC501C501u));
    asm("fma.rn.f16x2 %0, %1, %1, %2;" : "=r"(z) : "r"(y), "r"(0x46A146A1u));
    asm("fma.rn.f16x2 %0, %1, %1, %2;" : "=r"(r) : "r"(z), "r"(0x64006400u));
    return w - u + r;
}
__device__ __forceinline__ void softmax_fast(float (&s)[32], uint32_t (&p)[16], uint32_t cneg1) {
#pragma unroll
    for (int j = 0; j < 8; j++) {
        if (j & 1) {
            p[2 * j] = exp2_pair(s[4 * j], s[4 * j + 1], cneg1);
            p[2 * j + 1] = exp2_pair(s[4 * j + 2], s[4 * j + 3], cneg1);
        } else {
            p[2 * j] = packbf(ex2(s[4 * j]), ex2(s[4 * j + 1]));
            p[2 * j + 1] = packbf(ex2(s[4 * j + 2]), ex2(s[4 * j + 3]));
        }
    }
}

__device__ __forceinline__ void helper_cta(const Params& P, int e, char* sm) {
    const int t = threadIdx.x;
    if (t == 0) {
        const char* wo = (const char*)P.p_wo + e * (DM * DM * 2 / 4);
        for (int o = 0; o < DM * DM * 2 / 4; o += 14336) asm volatile("cp.async.bulk.prefetch.L2.global [%0], %1;" ::"l"(wo + o), "r"(14336));
    }
    float* red = (float*)sm;
    if (t < 448) {
        int c = t % 112, rg = t / 112;
        const __nv_bfloat16* W = (c < 56 ? P.p_wg : P.p_wu) + e * 448 + (c < 56 ? c : c - 56) * 8;
        float a[8];
#pragma unroll
        for (int i = 0; i < 8; i++) a[i] = 0.f;
#pragma unroll 14
        for (int r = rg; r < DM; r += 4) {
            uint4 v = __ldg((const uint4*)(W + (size_t)r * FF));
            a[0] += bflo(v.x); a[1] += bfhi(v.x); a[2] += bflo(v.y); a[3] += bfhi(v.y);
            a[4] += bflo(v.z); a[5] += bfhi(v.z); a[6] += bflo(v.w); a[7] += bfhi(v.w);
        }
#pragma unroll
        for (int i = 0; i < 8; i++) red[rg * 896 + c * 8 + i] = a[i];
    }
    nb_sync(NB_ALL, 512);
    for (int c = t; c < 896; c += 512) {
        float s = red[c] + red[896 + c] + red[2 * 896 + c] + red[3 * 896 + c];
        g_csgu[(c < 448 ? 0 : FF - 448) + e * 448 + c] = s;
    }
    nb_sync(NB_ALL, 512);
    if (t == 0) {
        flag_release(FL_CSGU);
        const char* wd = (const char*)P.p_wd + e * (FF * DM * 2 / 4);
        for (int o = 0; o < FF * DM * 2 / 4; o += 14336) asm volatile("cp.async.bulk.prefetch.L2.global [%0], %1;" ::"l"(wd + o), "r"(14336));
    }
}

__device__ __forceinline__ void producer_w(const Params& P, uint32_t sb, int i16) {
    Ring w{0, 0};
    const int ns = i16 & 7, ct = i16 % 7;
    const bool act = i16 < 14;
    auto acquire = [&]() -> uint32_t {
        mbar_wait(sb + SM_BAR + (B_WE + w.slot) * 8, w.par() ^ 1);
        uint32_t fb = sb + SM_BAR + (B_WF + w.slot) * 8;
        mbar_expect(fb, SLOT);
        return fb;
    };
#pragma unroll 1
    for (int l = 0; l < 2; l++) {
        w.slot = w.slot == 0 ? 0 : (w.slot <= 3 ? 3 : 0);
#pragma unroll 1
        for (int it = 0; it < 12; it++) {
            uint32_t fb = acquire();
            tma_ld2(sb + SM_W + w.slot * SLOT, &P.wqkv, ns * 168 + (it % 3 == 2 ? 112 : (it % 3) * 64), (it / 3) * 128, fb);
            w.adv<NWS>();
        }
        if (act) {
#pragma unroll 1
            for (int it = 0; it < 4; it++) {
                uint32_t fb = acquire();
                tma_ld3(sb + SM_W + w.slot * SLOT, &P.wo, ct * 64, 0, it * 4, fb);
                w.adv<NWS>();
            }
        }
#pragma unroll 1
        for (int it = 0; it < 28; it++) {
            int t = it / 7, kb = it - t * 7;
            int ch = t < 3 ? 8 * t + ns : 24 + (ns >> 1);
            uint32_t fb = acquire();
            tma_ld2(sb + SM_W + w.slot * SLOT, &P.wg, ch * 64, kb * 64, fb);
            tma_ld2(sb + SM_W + w.slot * SLOT + 8192, &P.wu, ch * 64, kb * 64, fb);
            w.adv<NWS>();
        }
        if (act) {
#pragma unroll 1
            for (int it = 0; it < 14; it++) {
                uint32_t fb = acquire();
                tma_ld2(sb + SM_W + w.slot * SLOT, &P.wd, ct * 64, it * 128, fb);
                w.adv<NWS>();
            }
        }
    }
}

template <class Need, class Issue>
__device__ __forceinline__ void gated_items(int n, int myflag, unsigned target, Ring& x, uint32_t sb, int lane, Need need, Issue issue) {
    bool rdy = myflag < 0;
    int next = 0;
    unsigned spins = 0;
    while (next < n) {
        if (!rdy) { rdy = (int)(flag_ld(myflag) - target) >= 0; if (rdy) fence_acq(); }
        unsigned m = __ballot_sync(0xffffffffu, rdy);
        while (next < n && (m & need(next)) == need(next)) {
            if (lane == 0) {
                fence_async_global();
                mbar_wait(sb + SM_BAR + (B_XE + x.slot) * 8, x.par() ^ 1);
                issue(next, sb + SM_X + x.slot * SLOT, sb + SM_BAR + (B_XF + x.slot) * 8);
            }
            x.adv<NXS>();
            next++;
        }
        __syncwarp();
        if (++spins > 4000000u) __trap();
    }
}

__device__ __forceinline__ void producer_a(const Params& P, uint32_t sb, char* sm, int vid, unsigned ep, int lane) {
    Ring x{0, 0};
#pragma unroll 1
    for (int l = 0; l < 2; l++) {
        asm volatile("" : "+r"(vid), "+r"(lane), "+r"(ep));
        const int g = vid >> 4, i16 = vid & 15;
        const int rb = 2 * g + (i16 >> 3);
        const int rbo = 2 * g + (i16 >= 7 ? 1 : 0);
        const bool act = i16 < 14;
        const int h = i16;
        {
            int fl = (l == 1 && lane < 7) ? FL_X + (1 * 16 + rb) * 8 + lane : -1;
            const CUtensorMap* tm = l == 0 ? &P.x_in : &P.x_ld;
            int r0 = (l == 0 ? 0 : SEQ) + rb * 128;
            gated_items(7, fl, 2 * ep, x, sb, lane, [](int k) { return 1u << k; },
                        [&](int k, uint32_t dst, uint32_t fb) { mbar_expect(fb, SLOT); tma_ld2(dst, tm, k * 64, r0, fb); });
            if (l == 1) nb_arrive(NB_PST, 96);
        }
        {
            if (lane < 2) flag_wait(FL_QKV + (l * 16 + 2 * g + lane) * 8 + h / 6, ep);
            __syncwarp();
            if (lane == 0) {
                fence_async_global();
                mbar_wait(sb + SM_BAR + (B_XE + x.slot) * 8, x.par() ^ 1);
                mbar_expect(sb + SM_BAR + B_QF * 8, SLOT);
                bulk_ld(sb + SM_STG, g_q + ((size_t)(l * 16 + h) * SEQ + g * 256) * 32, SLOT, sb + SM_BAR + B_QF * 8);
            }
            const int tile = (2 * g + (lane & 15)) & 15;
            int fl = FL_QKV + (l * 16 + tile) * 8 + ((lane < 16 ? 16 : 32) + h) / 6;
            const __nv_bfloat16* kvb = g_kv + (size_t)(l * 16 + h) * 16 * 8192;
            auto ldkv = [&](int k, uint32_t dst, uint32_t fb) { mbar_expect(fb, SLOT); bulk_ld(dst, kvb + (size_t)((2 * g + k) & 15) * 8192, SLOT, fb); };
            gated_items(15, fl, ep, x, sb, lane, [](int k) { return 0x10001u << k; }, ldkv);
            flag_wait(fl, ep);
            __syncwarp();
            float qn = 0.f, kn = 0.f;
            if (lane < 16) {
                float4 v = __ldcg((const float4*)&g_nrm[((l * 32 + 16 + h) * 16 + lane) * 4]);
                kn = fmaxf(fmaxf(v.x, v.y), fmaxf(v.z, v.w));
            } else if (lane < 18) {
                float4 v = __ldcg((const float4*)&g_nrm[((l * 32 + h) * 16 + 2 * g + lane - 16) * 4]);
                qn = fmaxf(fmaxf(v.x, v.y), fmaxf(v.z, v.w));
            }
            unsigned kb = __reduce_max_sync(0xffffffffu, __float_as_uint(kn)), qb = __reduce_max_sync(0xffffffffu, __float_as_uint(qn));
            const bool redo = !(__uint_as_float(kb) * __uint_as_float(qb) <= SAFE_BOUND2);
            if (lane == 0) *(volatile int*)(sm + SM_DEC) = redo ? 1 : 0;
            gated_items(1, -1, 0, x, sb, lane, [](int) { return 0u; }, [&](int, uint32_t dst, uint32_t fb) { ldkv(15, dst, fb); });
            if (redo) gated_items(16, -1, 0, x, sb, lane, [](int) { return 0u; }, ldkv);
        }
        if (act) {
            gated_items(8, lane == 0 ? FL_O + l * 16 + rbo : -1, 32 * ep, x, sb, lane, [](int) { return 1u; },
                        [&](int k, uint32_t dst, uint32_t fb) { mbar_expect(fb, SLOT); tma_ld2(dst, &P.o_ld, k * 64, l * SEQ + rbo * 128, fb); });
        }
        {
            if (lane == 0) flag_wait(FL_CSGU, 4 * ep);
            __syncwarp();
            gated_items(7, lane < 7 ? FL_X + (2 * l * 16 + rb) * 8 + lane : -1, 2 * ep, x, sb, lane, [](int k) { return 1u << k; },
                        [&](int k, uint32_t dst, uint32_t fb) { mbar_expect(fb, SLOT); tma_ld2(dst, &P.x_ld, k * 64, 2 * l * SEQ + rb * 128, fb); });
            nb_arrive(NB_PST, 96);
        }
        if (act) {
            gated_items(28, lane < 28 ? FL_H + (l * 16 + rbo) * 32 + lane : -1, 2 * ep, x, sb, lane, [](int k) { return 1u << k; },
                        [&](int k, uint32_t dst, uint32_t fb) { mbar_expect(fb, SLOT); tma_ld2(dst, &P.h_ld, k * 64, l * SEQ + rbo * 128, fb); });
        }
    }
}

__device__ __forceinline__ float2 combine_stats(const float2* p) {
    float4 a = __ldcg((const float4*)p), b = __ldcg((const float4*)p + 1), c = __ldcg((const float4*)p + 2);
    float2 d = __ldcg(p + 6);
    float mean = (a.x + a.z + b.x + b.z + c.x + c.z + d.x) * (1.f / 7.f);
    float m2 = a.y + a.w + b.y + b.w + c.y + c.w + d.y;
    float e0 = a.x - mean, e1 = a.z - mean, e2 = b.x - mean, e3 = b.z - mean, e4 = c.x - mean, e5 = c.z - mean, e6 = d.x - mean;
    m2 += 64.f * (e0 * e0 + e1 * e1 + e2 * e2 + e3 * e3 + e4 * e4 + e5 * e5 + e6 * e6);
    return make_float2(mean, rsqrtf(m2 * (1.f / DM) + 1e-5f));
}

__device__ __forceinline__ void stats_warps(uint32_t sb, char* sm, int g, int i16, unsigned ep, int t) {
    float2* s_stats = (float2*)(sm + SM_STATS);
    float* s_csq = (float*)(sm + SM_CSQ);
    const int rb = 2 * g + (i16 >> 3), ns = i16 & 7;
    flag_wait(FL_ST0 + rb, 8 * ep);
    s_stats[t] = __ldcg(&g_st0[rb * 128 + t]);
    s_stats[t + 64] = __ldcg(&g_st0[rb * 128 + t + 64]);
    flag_wait(FL_CSQ + ns, 16 * ep);
#pragma unroll 1
    for (int c = t; c < 168; c += 64) {
        float a = 0.f;
#pragma unroll
        for (int r = 0; r < 16; r++) a += __ldcg(&g_csp[r * 1344 + ns * 168 + c]);
        s_csq[c] = a;
    }
    mbar_arrive(sb + SM_BAR + B_ST * 8, 1);
#pragma unroll 1
    for (int b = 0; b < 3; b++) {
        nb_sync(NB_PST, 96);
#pragma unroll 1
        for (int r = t; r < 128; r += 64) s_stats[r] = combine_stats(&g_st[((size_t)b * SEQ + rb * 128 + r) * 8]);
        mbar_arrive(sb + SM_BAR + B_ST * 8, 1);
    }
}

template <int N> __device__ __forceinline__ void wgmma_qkv(float (&d)[N / 2], uint64_t da, uint64_t db);
template <> __device__ __forceinline__ void wgmma_qkv<112>(float (&d)[56], uint64_t da, uint64_t db) { wgmma_ss_112<1>(d, da, db); }
template <> __device__ __forceinline__ void wgmma_qkv<56>(float (&d)[28], uint64_t da, uint64_t db) { wgmma_ss_56<1>(d, da, db); }

template <int N>
__device__ __forceinline__ void qkv_phase(uint32_t sb, char* sm, Ring& x, Ring& w, int rh, int warp4, int lane, int ns) {
    constexpr int U0 = N == 112 ? 0 : 2, NU = N / 56, NA = N == 112 ? 2 : 1;
    const uint32_t xs0 = x.slot;
    const int q = lane & 3;
    float acc[N / 2];
    zero_regs(acc);
#pragma unroll 1
    for (int kb = 0; kb < 7; kb++) {
        mbar_wait(sb + SM_BAR + (B_XF + x.slot) * 8, x.par());
        if (!(kb & 1)) {
#pragma unroll
            for (int a = U0; a < U0 + NA; a++) mbar_wait(sb + SM_BAR + (B_WF + w.slot + a) * 8, (w.mask >> (w.slot + a)) & 1);
        }
        uint64_t da = mkdesc(sb + SM_X + x.slot * SLOT + rh * 8192, 16, 1024, 1);
        uint64_t db = mkdesc(sb + SM_W + (w.slot + U0) * SLOT + (kb & 1) * 8192, SLOT, 1024, 1);
        wg_fence();
#pragma unroll
        for (int k = 0; k < 4; k++) wgmma_qkv<N>(acc, da + k * 2, db + k * 128);
        wg_commit();
        if (kb > 0 && !(kb & 1)) {
            wg_wait<1>();
            if (lane < NA) mbar_arrive(sb + SM_BAR + (B_WE + (3 - w.slot) + U0 + lane) * 8, 2);
        }
        x.adv<NXS>();
        if ((kb & 1) || kb == 6) w.skip<NWS>(3);
    }
    wg_wait<0>();
    fence_regs(acc);
    if (lane < NA) mbar_arrive(sb + SM_BAR + (B_WE + (3 - w.slot) + U0 + lane) * 8, 2);
    mbar_wait(sb + SM_BAR + B_ST * 8, 0);
    nb_sync(NB_ALL, 512);
    if (lane < 4) mbar_arrive(sb + SM_BAR + (B_XE + wrap7(xs0 + lane)) * 8, 1);
    const int r = rh * 64 + warp4 * 16 + (lane >> 2), sw = (r >> 1) & 3;
    const float2 st0 = ((const float2*)(sm + SM_STATS))[r], st1 = ((const float2*)(sm + SM_STATS))[r + 8];
    const float* s_csq = (const float*)(sm + SM_CSQ);
    uint32_t off[7];
#pragma unroll
    for (int j = 0; j < 7; j++) {
        int c = 8 * j + 2 * q, o = c >= 28 ? 8192 : 0;
        c = c >= 28 ? c - 28 : c;
        off[j] = o + r * 64 + (((c >> 3) ^ sw) << 4) + (c & 7) * 2;
    }
#pragma unroll
    for (int u = 0; u < NU; u++) {
        const float sc = (ns * 6 + 2 * (U0 + u) < 16) ? 0.18898223650461362f * 1.4426950408889634f : 1.f;
        const float a0 = st0.y * sc, a1 = st1.y * sc;
        const uint32_t base = sb + SM_X + wrap7(xs0 + 4 + U0 + u) * SLOT;
#pragma unroll
        for (int j = 0; j < 7; j++) {
            const int jj = u * 7 + j;
            const float2 cs = *(const float2*)(s_csq + (U0 * 7 + jj) * 8 + 2 * q);
            sts32(base + off[j], packbf((acc[4 * jj] - st0.x * cs.x) * a0, (acc[4 * jj + 1] - st0.x * cs.y) * a0));
            sts32(base + off[j] + 512, packbf((acc[4 * jj + 2] - st1.x * cs.x) * a1, (acc[4 * jj + 3] - st1.x * cs.y) * a1));
        }
    }
    if (N == 56) {
        const int pr = warp4 * 32 + lane;
#pragma unroll
        for (int u = 0; u < 3; u++) {
            const int ty = (ns * 6 + 2 * u) >> 4;
            const uint32_t v = ty == 1 ? ((pr & 8) ? K_POLY_BITS : K_MUFU_BITS) : ONE_BITS;
            const uint32_t a = sb + SM_X + wrap7(xs0 + 4 + u) * SLOT + rh * 8192 + pr * 64 + ((3 ^ ((pr >> 1) & 3)) << 4) + 8;
            asm volatile("st.shared.v2.b32 [%0], {%1, %2};" ::"r"(a), "r"(v), "r"(0) : "memory");
        }
    }
}

template <int NKB>
__device__ __forceinline__ void proj_phase(uint32_t sb, Ring& x, Ring& w, int wg, int warp4, int lane, const __nv_bfloat16* res,
                                           const CUtensorMap* st_map, int st_row, int ct, float2* stats_out, int flag_idx, bool wait_stg) {
    float acc[32];
    zero_regs(acc);
    uint32_t pk[16];
    const int q = lane & 3, rl = wg * 64 + warp4 * 16 + (lane >> 2);
    {
        const uint32_t* r0 = (const uint32_t*)(res + (size_t)rl * DM + ct * 64) + q;
#pragma unroll
        for (int j = 0; j < 8; j++) { pk[2 * j] = __ldcg(r0 + j * 4); pk[2 * j + 1] = __ldcg(r0 + 8 * DM / 2 + j * 4); }
    }
    uint32_t px = 0, pw = 0;
#pragma unroll 1
    for (int kb = 0; kb < NKB; kb++) {
        mbar_wait(sb + SM_BAR + (B_XF + x.slot) * 8, x.par());
        if (!(kb & 1)) mbar_wait(sb + SM_BAR + (B_WF + w.slot) * 8, w.par());
        uint64_t da = mkdesc(sb + SM_X + x.slot * SLOT + wg * 8192, 16, 1024, 1);
        uint64_t db = mkdesc(sb + SM_W + w.slot * SLOT + (kb & 1) * 8192, 8192, 1024, 1);
        wg_fence();
#pragma unroll
        for (int k = 0; k < 4; k++) wgmma_ss_64<1>(acc, da + k * 2, db + k * 128);
        wg_commit();
        if (kb > 0) {
            wg_wait<1>();
            if (lane == 0) {
                mbar_arrive(sb + SM_BAR + (B_XE + px) * 8, 2);
                if (!(kb & 1)) mbar_arrive(sb + SM_BAR + (B_WE + pw) * 8, 2);
            }
        }
        px = x.slot; pw = w.slot;
        x.adv<NXS>();
        if (kb & 1) w.adv<NWS>();
    }
    nb_arrive(NB_SKIP, 512);
    wg_wait<0>();
    fence_regs(acc);
    if (lane == 0) { mbar_arrive(sb + SM_BAR + (B_XE + px) * 8, 2); mbar_arrive(sb + SM_BAR + (B_WE + pw) * 8, 2); }
#pragma unroll
    for (int j = 0; j < 8; j++) {
        pk[2 * j] = packbf(acc[4 * j] + bflo(pk[2 * j]), acc[4 * j + 1] + bfhi(pk[2 * j]));
        pk[2 * j + 1] = packbf(acc[4 * j + 2] + bflo(pk[2 * j + 1]), acc[4 * j + 3] + bfhi(pk[2 * j + 1]));
    }
    if (wait_stg) mbar_wait(sb + SM_BAR + (B_STG + wg) * 8, 1);
    {
        const int r = warp4 * 16 + (lane & 7) + ((lane >> 3) & 1) * 8, cs = lane >> 4;
        const uint32_t base = sb + SM_STG + wg * 8192 + r * 128;
#pragma unroll
        for (int j = 0; j < 8; j += 2) stsm4(base + (((j + cs) ^ (r & 7)) << 4), pk[2 * j], pk[2 * j + 1], pk[2 * j + 2], pk[2 * j + 3]);
    }
    fence_async_smem();
    nb_sync(NB_WG + wg, 128);
    const bool issuer = warp4 == 0 && lane == 0;
    if (issuer) { tma_st2(st_map, ct * 64, st_row + wg * 64, sb + SM_STG + wg * 8192); bulk_commit(); }
    if (stats_out) {
        float s0 = 0.f, s1 = 0.f;
#pragma unroll
        for (int j = 0; j < 8; j++) { s0 += bflo(pk[2 * j]) + bfhi(pk[2 * j]); s1 += bflo(pk[2 * j + 1]) + bfhi(pk[2 * j + 1]); }
        s0 += __shfl_xor_sync(0xffffffffu, s0, 1); s1 += __shfl_xor_sync(0xffffffffu, s1, 1);
        s0 += __shfl_xor_sync(0xffffffffu, s0, 2); s1 += __shfl_xor_sync(0xffffffffu, s1, 2);
        s0 *= 1.f / 64.f; s1 *= 1.f / 64.f;
        float m0 = 0.f, m1 = 0.f;
#pragma unroll
        for (int j = 0; j < 8; j++) {
            float a = bflo(pk[2 * j]) - s0, b = bfhi(pk[2 * j]) - s0, c = bflo(pk[2 * j + 1]) - s1, d = bfhi(pk[2 * j + 1]) - s1;
            m0 += a * a + b * b; m1 += c * c + d * d;
        }
        m0 += __shfl_xor_sync(0xffffffffu, m0, 1); m1 += __shfl_xor_sync(0xffffffffu, m1, 1);
        m0 += __shfl_xor_sync(0xffffffffu, m0, 2); m1 += __shfl_xor_sync(0xffffffffu, m1, 2);
        if (q == 0) { stats_out[(size_t)rl * 8 + ct] = make_float2(s0, m0); stats_out[(size_t)(rl + 8) * 8 + ct] = make_float2(s1, m1); }
        nb_sync(NB_WG + wg, 128);
    }
    if (issuer) { bulk_wait_all(); if (flag_idx >= 0) flag_release(flag_idx); }
}

#define PHASE_VARS                                                                                          \
    int tid, vid = vid_in;                                                                                  \
    asm volatile("mov.u32 %0, %%tid.x;" : "=r"(tid));                                                       \
    asm volatile("" : "+r"(vid));                                                                           \
    const int wg = __shfl_sync(0xffffffffu, tid >> 7, 0), warp4 = (tid >> 5) & 3, lane = tid & 31, q = lane & 3; \
    const int g = vid >> 4, i16 = vid & 15, ns = i16 & 7;                                                   \
    const int rb = 2 * g + (i16 >> 3), rbo = 2 * g + (i16 >= 7 ? 1 : 0), ct = i16 >= 7 ? i16 - 7 : i16;     \
    const bool act = i16 < 14, issuer = (tid & 127) == 0;                                                   \
    (void)wg; (void)warp4; (void)q; (void)ns; (void)rb; (void)rbo; (void)ct; (void)act; (void)issuer;

__device__ __forceinline__ void consumer(const Params& P, uint32_t sb, char* sm, const int vid_in) {
    Ring x{0, 0}, w{0, 0};
    const float2* s_stats = (const float2*)(sm + SM_STATS);

    {
        PHASE_VARS
        const int row = rb * 128 + ns * 16 + (tid >> 5);
        const uint32_t* xr = (const uint32_t*)(P.x + (size_t)row * DM) + lane;
        uint32_t v[7];
#pragma unroll
        for (int j = 0; j < 7; j++) v[j] = __ldg(xr + j * 32);
        uint4 wa = make_uint4(0, 0, 0, 0), wb = wa;
        const int c = tid % 21, rr = tid / 21;
        if (rr < 14) {
            const __nv_bfloat16* wp = P.p_wqkv + (size_t)(rb * 28 + rr) * 1344 + ns * 168 + c * 8;
            wa = __ldg((const uint4*)wp); wb = __ldg((const uint4*)(wp + 14 * 1344));
        }
        float s = 0.f;
#pragma unroll
        for (int j = 0; j < 7; j++) s += bflo(v[j]) + bfhi(v[j]);
#pragma unroll
        for (int o = 16; o; o >>= 1) s += __shfl_xor_sync(0xffffffffu, s, o);
        s *= 1.f / DM;
        float m = 0.f;
#pragma unroll
        for (int j = 0; j < 7; j++) { float a = bflo(v[j]) - s, b = bfhi(v[j]) - s; m += a * a + b * b; }
#pragma unroll
        for (int o = 16; o; o >>= 1) m += __shfl_xor_sync(0xffffffffu, m, o);
        if (lane == 0) g_st0[row] = make_float2(s, rsqrtf(m * (1.f / DM) + 1e-5f));
        float* red = (float*)(sm + SM_STG);
        if (rr < 14) {
            float4* d = (float4*)(red + rr * 168 + c * 8);
            d[0] = make_float4(bflo(wa.x) + bflo(wb.x), bfhi(wa.x) + bfhi(wb.x), bflo(wa.y) + bflo(wb.y), bfhi(wa.y) + bfhi(wb.y));
            d[1] = make_float4(bflo(wa.z) + bflo(wb.z), bfhi(wa.z) + bfhi(wb.z), bflo(wa.w) + bflo(wb.w), bfhi(wa.w) + bfhi(wb.w));
        }
        nb_sync(NB_ALL, 512);
        if (wg >= 2) {
            const int t = tid - 256;
            if (t < 168) {
                float a = 0.f;
#pragma unroll
                for (int r = 0; r < 14; r++) a += red[r * 168 + t];
                g_csp[rb * 1344 + ns * 168 + t] = a;
            }
            nb_sync(NB_STAT, 256);
            if (t == 0) { flag_release(FL_ST0 + rb); flag_release(FL_CSQ + ns); }
        }
    }

#pragma unroll 1
    for (int l = 0; l < 2; l++) {
        {
        PHASE_VARS
        if (tid == 0) TS(l * 16 + 0);
        w.slot = w.slot == 0 ? 0 : (w.slot <= 3 ? 3 : 0);
        const uint32_t xs0 = x.slot;
        if (wg < 2) qkv_phase<112>(sb, sm, x, w, wg, warp4, lane, ns);
        else qkv_phase<56>(sb, sm, x, w, wg - 2, warp4, lane, ns);
        if (tid == 0) TS(l * 16 + 1);
        fence_async_smem();
        nb_sync(NB_ALL, 512);
        if (tid == 0) {
#pragma unroll 1
            for (int t = 0; t < 6; t++) {
                const int T = ns * 6 + t, ty = T >> 4, hh = T & 15;
                __nv_bfloat16* dst = ty == 0 ? g_q + ((size_t)(l * 16 + hh) * SEQ + rb * 128) * 32
                                             : g_kv + ((size_t)((l * 16 + hh) * 16 + rb) * 2 + (ty - 1)) * 4096;
                bulk_st(dst, sb + SM_X + wrap7(xs0 + 4 + (t >> 1)) * SLOT + (t & 1) * 8192, 8192);
            }
            bulk_commit();
        }
#pragma unroll 1
        for (int it = tid; it < 768; it += 512) {
            const int t = it >> 7, r = it & 127, T = ns * 6 + t;
            if (T < 32) {
                const char* rowp = sm + SM_X + wrap7(xs0 + 4 + (t >> 1)) * SLOT + (t & 1) * 8192 + r * 64;
                float n2 = 0.f;
#pragma unroll
                for (int c = 0; c < 4; c++) {
                    uint4 v = *(const uint4*)(rowp + ((c ^ ((r >> 1) & 3)) << 4));
                    n2 += bflo(v.x) * bflo(v.x) + bfhi(v.x) * bfhi(v.x) + bflo(v.y) * bflo(v.y) + bfhi(v.y) * bfhi(v.y);
                    if (c < 3) n2 += bflo(v.z) * bflo(v.z) + bfhi(v.z) * bfhi(v.z) + bflo(v.w) * bflo(v.w) + bfhi(v.w) * bfhi(v.w);
                }
                unsigned mx = __reduce_max_sync(0xffffffffu, __float_as_uint(n2) & 0x7FFFFFFFu);
                if (lane == 0) g_nrm[((l * 32 + T) * 16 + rb) * 4 + (r >> 5)] = __uint_as_float(mx > 0x7F800000u ? 0x7F800000u : mx);
            }
        }
        nb_sync(NB_ALL, 512);
        if (tid == 0) {
            bulk_wait_all();
#pragma unroll
            for (int u = 0; u < 3; u++) mbar_arrive(sb + SM_BAR + (B_XE + wrap7(xs0 + 4 + u)) * 8, 16);
            flag_release(FL_QKV + (l * 16 + rb) * 8 + ns);
            TS(l * 16 + 2);
        }
        }

        {
            const bool lane0 = (threadIdx.x & 31) == 0;
            x.uniform(); w.uniform();
            mbar_wait(sb + SM_BAR + B_QF * 8, l);
            const uint64_t qd = mkdesc(sb + SM_STG + __shfl_sync(0xffffffffu, threadIdx.x >> 7, 0) * 4096, 16, 512, 2);
            uint32_t cneg1 = 0xBC00BC00u;
            asm volatile("" : "+r"(cneg1));
            float o[16];
#pragma unroll
            for (int i = 0; i < 16; i++) o[i] = 0.f;
            fence_regs(o);
            const uint64_t kd0 = mkdesc(sb + SM_X, 16, 512, 2), vd0 = mkdesc(sb + SM_X + 8192, 512, 512, 2);
            {
                float s[32];
                uint32_t p0[16], p1[16];
                mbar_wait(sb + SM_BAR + (B_XF + x.slot) * 8, x.par());
                { PHASE_VARS if (tid == 0) TS(l * 16 + 3); }
                wg_fence();
                wgmma_ssz_64<0>(s, qd, kd0 + x.slot * 1024);
                wgmma_ss_64<0>(s, qd + 2, kd0 + x.slot * 1024 + 2);
                wg_commit(); wg_wait<0>(); fence_regs(s);
                softmax_fast(s, p0, cneg1);
#pragma unroll 1
                for (int j = 0; j < 16; j++) {
                    const uint32_t cur = x.slot;
                    const uint64_t kd = kd0 + cur * 1024, vd = vd0 + cur * 1024;
                    wg_fence();
                    wgmma_ssz_64<0>(s, qd, kd + 256);
                    wgmma_ss_64<0>(s, qd + 2, kd + 258);
                    wg_commit();
#pragma unroll
                    for (int k = 0; k < 4; k++) wgmma_rs_32<1>(o, p0[4 * k], p0[4 * k + 1], p0[4 * k + 2], p0[4 * k + 3], vd + k * 64);
                    wg_commit();
                    wg_wait<1>(); fence_regs(s);
                    softmax_fast(s, p1, cneg1);
                    wg_wait<0>(); fence_regs(o); fence_regs(p0);
                    x.adv<NXS>();
                    if (j < 15) mbar_wait(sb + SM_BAR + (B_XF + x.slot) * 8, x.par());
                    const uint64_t kn = kd0 + (j < 15 ? x.slot : cur) * 1024;
                    wg_fence();
                    wgmma_ssz_64<0>(s, qd, kn);
                    wgmma_ss_64<0>(s, qd + 2, kn + 2);
                    wg_commit();
#pragma unroll
                    for (int k = 0; k < 4; k++) wgmma_rs_32<1>(o, p1[4 * k], p1[4 * k + 1], p1[4 * k + 2], p1[4 * k + 3], vd + 256 + k * 64);
                    wg_commit();
                    wg_wait<1>(); fence_regs(s);
                    softmax_fast(s, p0, cneg1);
                    wg_wait<0>(); fence_regs(o); fence_regs(p1);
                    if (lane0) mbar_arrive(sb + SM_BAR + (B_XE + cur) * 8, 1);
                }
            }
            PHASE_VARS
            if (*(volatile int*)(sm + SM_DEC)) {
                uint32_t qf[8];
                {
                    const int r = warp4 * 16 + (lane & 7) + ((lane >> 3) & 1) * 8, cs = lane >> 4;
                    const uint32_t base = sb + SM_STG + wg * 4096 + r * 64;
                    ldsm4(base + (((0 + cs) ^ ((r >> 1) & 3)) << 4), qf[0], qf[1], qf[2], qf[3]);
                    ldsm4(base + (((2 + cs) ^ ((r >> 1) & 3)) << 4), qf[4], qf[5], qf[6], qf[7]);
                }
                if (q == 2) { qf[6] &= 0xFFFF0000u; qf[7] &= 0xFFFF0000u; }
#pragma unroll
                for (int i = 0; i < 16; i++) o[i] = 0.f;
                float m0 = -INFINITY, m1 = -INFINITY;
#pragma unroll 1
                for (int j = 0; j < 32; j++) {
                    float s[32];
                    uint32_t p[16];
                    if (!(j & 1)) mbar_wait(sb + SM_BAR + (B_XF + x.slot) * 8, x.par());
                    const uint64_t kd = kd0 + x.slot * 1024 + (j & 1) * 256, vd = vd0 + x.slot * 1024 + (j & 1) * 256;
                    wg_fence();
                    wgmma_rsz_64<0>(s, qf[0], qf[1], qf[2], qf[3], kd);
                    wgmma_rs_64<0>(s, qf[4], qf[5], qf[6], qf[7], kd + 2);
                    wg_commit(); wg_wait<0>(); fence_regs(s);
                    float n0 = m0, n1 = m1;
#pragma unroll
                    for (int i = 0; i < 8; i++) { n0 = fmaxf(n0, fmaxf(s[4 * i], s[4 * i + 1])); n1 = fmaxf(n1, fmaxf(s[4 * i + 2], s[4 * i + 3])); }
                    n0 = fmaxf(n0, __shfl_xor_sync(0xffffffffu, n0, 1)); n1 = fmaxf(n1, __shfl_xor_sync(0xffffffffu, n1, 1));
                    n0 = fmaxf(n0, __shfl_xor_sync(0xffffffffu, n0, 2)); n1 = fmaxf(n1, __shfl_xor_sync(0xffffffffu, n1, 2));
                    const float c0 = ex2(m0 - n0), c1 = ex2(m1 - n1);
                    m0 = n0; m1 = n1;
#pragma unroll
                    for (int i = 0; i < 4; i++) { o[4 * i] *= c0; o[4 * i + 1] *= c0; o[4 * i + 2] *= c1; o[4 * i + 3] *= c1; }
#pragma unroll
                    for (int i = 0; i < 8; i++) {
                        p[2 * i] = packbf(ex2(s[4 * i] - m0), ex2(s[4 * i + 1] - m0));
                        p[2 * i + 1] = packbf(ex2(s[4 * i + 2] - m1), ex2(s[4 * i + 3] - m1));
                    }
                    fence_regs(o);
                    wg_fence();
#pragma unroll
                    for (int k = 0; k < 4; k++) wgmma_rs_32<1>(o, p[4 * k], p[4 * k + 1], p[4 * k + 2], p[4 * k + 3], vd + k * 64);
                    wg_commit(); wg_wait<0>(); fence_regs(o);
                    if (j & 1) { if (lane == 0) mbar_arrive(sb + SM_BAR + (B_XE + x.slot) * 8, 1); x.adv<NXS>(); }
                }
            }
            if (tid == 0) TS(l * 16 + 4);
            nb_sync(NB_WG + wg, 128);
            const float i0 = 1.f / __shfl_sync(0xffffffffu, o[12], (lane & ~3) | 2), i1 = 1.f / __shfl_sync(0xffffffffu, o[14], (lane & ~3) | 2);
            {
                const int r = warp4 * 16 + (lane & 7) + ((lane >> 3) & 1) * 8, cs = lane >> 4;
                const uint32_t base = sb + SM_STG + wg * 4096 + r * 64;
                stsm4(base + (((0 + cs) ^ ((r >> 1) & 3)) << 4), packbf(o[0] * i0, o[1] * i0), packbf(o[2] * i1, o[3] * i1), packbf(o[4] * i0, o[5] * i0), packbf(o[6] * i1, o[7] * i1));
                stsm4(base + (((2 + cs) ^ ((r >> 1) & 3)) << 4), packbf(o[8] * i0, o[9] * i0), packbf(o[10] * i1, o[11] * i1),
                      q < 2 ? packbf(o[12] * i0, o[13] * i0) : 0u, q < 2 ? packbf(o[14] * i1, o[15] * i1) : 0u);
            }
            fence_async_smem();
            nb_sync(NB_WG + wg, 128);
            if (issuer) {
                tma_st2(&P.o_st, i16 * 32, l * SEQ + g * 256 + wg * 64, sb + SM_STG + wg * 4096);
                bulk_commit(); bulk_wait_all();
                flag_release(FL_O + l * 16 + 2 * g + (wg >> 1));
            }
            nb_sync(NB_ALL, 512);
            if (tid == 0) TS(l * 16 + 5);
        }

        {
        PHASE_VARS
        if (act) {
            if (wg < 2) {
                const __nv_bfloat16* res = (l == 0 ? P.x : g_x + (size_t)SEQ * DM) + (size_t)rbo * 128 * DM;
                proj_phase<8>(sb, x, w, wg, warp4, lane, res, &P.x_st, 2 * l * SEQ + rbo * 128, ct,
                              &g_st[((size_t)2 * l * SEQ + rbo * 128) * 8], FL_X + (2 * l * 16 + rbo) * 8 + ct, false);
            } else {
                x.skip<NXS>(8); w.skip<NWS>(4);
                nb_sync(NB_SKIP, 512);
            }
        }
        if (tid == 0) TS(l * 16 + 6);
        }

        {
            PHASE_VARS
            const int pr = wg >> 1, rh = wg & 1;
            const uint32_t a0 = x.slot, amask = x.mask;
            x.skip<NXS>(7);
            if (pr == 1) w.skip<NWS>(7);
#pragma unroll 1
            for (int t = pr; t < 4; t += 2) {
                const bool work = t < 3 || rh == (ns & 1);
                const bool lastA = t == 2 || t == 3 || (t == 1 && rh != (ns & 1));
                float acc[64];
                zero_regs(acc);
                if (t > 0) nb_sync(pr ? NB_ORD0 : NB_ORD1, 512);
                if (work) {
                    uint32_t pw = 0, pa = 0;
#pragma unroll 1
                    for (int kb = 0; kb < 7; kb++) {
                        const uint32_t as = wrap7(a0 + kb);
                        if (t < 2) mbar_wait(sb + SM_BAR + (B_XF + as) * 8, (amask >> as) & 1);
                        mbar_wait(sb + SM_BAR + (B_WF + w.slot) * 8, w.par());
                        uint64_t da = mkdesc(sb + SM_X + as * SLOT + rh * 8192, 16, 1024, 1);
                        uint64_t db = mkdesc(sb + SM_W + w.slot * SLOT, 8192, 1024, 1);
                        wg_fence();
#pragma unroll
                        for (int k = 0; k < 4; k++) wgmma_ss_128<1>(acc, da + k * 2, db + k * 128);
                        wg_commit();
                        if (kb > 0) {
                            wg_wait<1>();
                            if (lane == 0) {
                                mbar_arrive(sb + SM_BAR + (B_WE + pw) * 8, t < 3 ? 2 : 4);
                                if (lastA) mbar_arrive(sb + SM_BAR + (B_XE + pa) * 8, 1);
                            }
                        }
                        pw = w.slot; pa = as;
                        w.adv<NWS>();
                    }
                    nb_arrive(pr ? NB_ORD1 : NB_ORD0, 512);
                    wg_wait<0>();
                    fence_regs(acc);
                    if (lane == 0) {
                        mbar_arrive(sb + SM_BAR + (B_WE + pw) * 8, t < 3 ? 2 : 4);
                        if (lastA) mbar_arrive(sb + SM_BAR + (B_XE + pa) * 8, 1);
                    }
                } else {
                    w.skip<NWS>(7);
                    nb_arrive(NB_ORD1, 512);
                }
                if (t < 3) w.skip<NWS>(7);
                if (t < 2) mbar_wait(sb + SM_BAR + B_ST * 8, 1);
                if (t > 0) mbar_wait(sb + SM_BAR + (B_STG + rh) * 8, (t - 1) & 1);
                if (work) {
                    PHASE_VARS
                    const int ch = t < 3 ? 8 * t + ns : 24 + (ns >> 1);
                    const int r = rh * 64 + warp4 * 16 + (lane >> 2);
                    const float2 st0 = s_stats[r], st1 = s_stats[r + 8];
                    const float g0 = -1.4426950408889634f * st0.y, g1 = -1.4426950408889634f * st1.y;
                    const float2* cg = (const float2*)(g_csgu + ch * 64) + q;
                    const int sr = warp4 * 16 + (lane & 7) + ((lane >> 3) & 1) * 8, cs = lane >> 4;
                    const uint32_t base = sb + SM_STG + rh * 8192 + sr * 128;
#pragma unroll
                    for (int jj = 0; jj < 8; jj += 2) {
                        uint32_t pk[4];
#pragma unroll
                        for (int j = jj; j < jj + 2; j++) {
                            const float2 a = __ldca(cg + j * 4), b = __ldca(cg + FF / 2 + j * 4);
                            float h0 = (acc[32 + 4 * j] - st0.x * b.x) * st0.y * rcp(1.f + ex2((acc[4 * j] - st0.x * a.x) * g0));
                            float h1 = (acc[32 + 4 * j + 1] - st0.x * b.y) * st0.y * rcp(1.f + ex2((acc[4 * j + 1] - st0.x * a.y) * g0));
                            float h2 = (acc[32 + 4 * j + 2] - st1.x * b.x) * st1.y * rcp(1.f + ex2((acc[4 * j + 2] - st1.x * a.x) * g1));
                            float h3 = (acc[32 + 4 * j + 3] - st1.x * b.y) * st1.y * rcp(1.f + ex2((acc[4 * j + 3] - st1.x * a.y) * g1));
                            pk[2 * (j - jj)] = packbf(h0, h1); pk[2 * (j - jj) + 1] = packbf(h2, h3);
                        }
                        stsm4(base + (((jj + cs) ^ (sr & 7)) << 4), pk[0], pk[1], pk[2], pk[3]);
                    }
                    fence_async_smem();
                    nb_sync(NB_WG + wg, 128);
                    if (issuer) {
                        tma_st2(&P.h_st, ch * 64, l * SEQ + rb * 128 + rh * 64, sb + SM_STG + rh * 8192);
                        bulk_commit(); bulk_wait_all();
                        mbar_arrive(sb + SM_BAR + (B_STG + rh) * 8, 1);
                        flag_release(FL_H + (l * 16 + rb) * 32 + ch);
                    }
                } else if (issuer) {
                    mbar_arrive(sb + SM_BAR + (B_STG + rh) * 8, 1);
                }
            }
            if (pr == 0) nb_sync(NB_ORD1, 512);
            if (tid == 0) TS(l * 16 + 7);
        }

        {
        PHASE_VARS
        if (act) {
            if (wg < 2) {
                const __nv_bfloat16* res = g_x + ((size_t)2 * l * SEQ + rbo * 128) * DM;
                proj_phase<28>(sb, x, w, wg, warp4, lane, res, l == 0 ? &P.x_st : &P.out_st, (l == 0 ? SEQ : 0) + rbo * 128, ct,
                               l == 0 ? &g_st[((size_t)SEQ + rbo * 128) * 8] : nullptr, l == 0 ? FL_X + (16 + rbo) * 8 + ct : -1, true);
            } else {
                x.skip<NXS>(28); w.skip<NWS>(14);
                nb_sync(NB_SKIP, 512);
            }
        }
        if (tid == 0) TS(l * 16 + 8);
        }
    }
}

__device__ __forceinline__ int vid_from_smid(unsigned s) {
    if (s < 64) return ((s >> 1) & 7) * 16 + (s >> 4) * 2 + (s & 1);
    if (s < 120) { unsigned t = s - 64; return (1 + (t % 14) / 2) * 16 + 8 + (t / 14) * 2 + (t & 1); }
    if (s < 124) return 128 + (s - 120);
    return 8 + (s - 124);
}

__global__ void __launch_bounds__(NTHREADS, 1) fused_layers_kernel(const __grid_constant__ Params P) {
    extern __shared__ __align__(1024) char sm[];
    const uint32_t sb = s2u(sm);
    int vid = blockIdx.x;
    if (P.use_smid) { unsigned s; asm volatile("mov.u32 %0, %%smid;" : "=r"(s)); vid = vid_from_smid(s); }
    const unsigned ep = *(volatile unsigned*)&g_epoch + 1;
    if (threadIdx.x == 0) {
        TS(63);
        if (sb & 1023) __trap();
        for (int i = 0; i < NXS; i++) { mbar_init(sb + SM_BAR + (B_XF + i) * 8, 1); mbar_init(sb + SM_BAR + (B_XE + i) * 8, 16); }
        for (int i = 0; i < NWS; i++) { mbar_init(sb + SM_BAR + (B_WF + i) * 8, 1); mbar_init(sb + SM_BAR + (B_WE + i) * 8, 16); }
        mbar_init(sb + SM_BAR + B_QF * 8, 1);
        mbar_init(sb + SM_BAR + B_ST * 8, 64);
        mbar_init(sb + SM_BAR + B_STG * 8, 1); mbar_init(sb + SM_BAR + (B_STG + 1) * 8, 1);
        fence_async_smem();
    }
    __syncthreads();
    if (threadIdx.x >= 512) {
        asm volatile("setmaxnreg.dec.sync.aligned.u32 32;");
        const int warp = threadIdx.x >> 5, lane = threadIdx.x & 31;
        if (vid < 128) {
            if (warp == 16) producer_a(P, sb, sm, vid, ep, lane);
            else if (warp == 17) { if (lane == 0) producer_w(P, sb, vid & 15); }
            else stats_warps(sb, sm, vid >> 4, vid & 15, ep, threadIdx.x - 576);
        }
    } else {
        asm volatile("setmaxnreg.inc.sync.aligned.u32 112;");
        if (vid < 128) consumer(P, sb, sm, vid);
        else helper_cta(P, vid - 128, sm);
        if (threadIdx.x == 0) {
            unsigned old = atomicAdd(&g_done, 1) + 1;
            if (old % NCTA == 0) *(volatile unsigned*)&g_epoch = old / NCTA;
        }
    }
}

typedef CUresult (*EncodeFn)(CUtensorMap*, CUtensorMapDataType, cuuint32_t, void*, const cuuint64_t*, const cuuint64_t*, const cuuint32_t*,
                             const cuuint32_t*, CUtensorMapInterleave, CUtensorMapSwizzle, CUtensorMapL2promotion, CUtensorMapFloatOOBfill);

static void enc2(EncodeFn f, CUtensorMap* m, const void* p, int cols, int rows, int bc, int br, CUtensorMapSwizzle sw) {
    cuuint64_t gd[2] = {(cuuint64_t)cols, (cuuint64_t)rows}, gs[1] = {(cuuint64_t)cols * 2};
    cuuint32_t bd[2] = {(cuuint32_t)bc, (cuuint32_t)br}, es[2] = {1, 1};
    f(m, CU_TENSOR_MAP_DATA_TYPE_BFLOAT16, 2, (void*)p, gd, gs, bd, es, CU_TENSOR_MAP_INTERLEAVE_NONE, sw, CU_TENSOR_MAP_L2_PROMOTION_L2_128B,
      CU_TENSOR_MAP_FLOAT_OOB_FILL_NONE);
}

extern "C" void kernel_launch(void* const* d_in, const int* in_sizes, int n_in, void* d_out, int out_size) {
    (void)in_sizes; (void)n_in; (void)out_size;
    static EncodeFn enc = nullptr;
    static int sms = 0;
    if (!enc) {
        void* fn = nullptr;
        cudaDriverEntryPointQueryResult qr;
        cudaGetDriverEntryPoint("cuTensorMapEncodeTiled", &fn, cudaEnableDefault, &qr);
        enc = (EncodeFn)fn;
        cudaFuncSetAttribute(fused_layers_kernel, cudaFuncAttributeMaxDynamicSharedMemorySize, SM_TOTAL);
        int dev = 0;
        cudaGetDevice(&dev);
        cudaDeviceGetAttribute(&sms, cudaDevAttrMultiProcessorCount, dev);
    }
    void *px, *ph, *po;
    cudaGetSymbolAddress(&px, g_x); cudaGetSymbolAddress(&ph, g_h); cudaGetSymbolAddress(&po, g_o);
    Params P;
    const auto S128 = CU_TENSOR_MAP_SWIZZLE_128B;
    enc2(enc, &P.x_in, d_in[0], DM, SEQ, 64, 128, S128);
    enc2(enc, &P.x_ld, px, DM, 3 * SEQ, 64, 128, S128);
    enc2(enc, &P.x_st, px, DM, 3 * SEQ, 64, 64, S128);
    enc2(enc, &P.out_st, d_out, DM, SEQ, 64, 64, S128);
    enc2(enc, &P.h_ld, ph, FF, 2 * SEQ, 64, 128, S128);
    enc2(enc, &P.h_st, ph, FF, 2 * SEQ, 64, 64, S128);
    enc2(enc, &P.o_ld, po, 512, 2 * SEQ, 64, 128, S128);
    enc2(enc, &P.o_st, po, 512, 2 * SEQ, 32, 64, CU_TENSOR_MAP_SWIZZLE_64B);
    enc2(enc, &P.wqkv, d_in[1], 1344, DM, 64, 128, S128);
    {
        cuuint64_t gd[3] = {DM, 28, 16}, gs[2] = {DM * 2, 28 * DM * 2};
        cuuint32_t bd[3] = {64, 32, 4}, es[3] = {1, 1, 1};
        enc(&P.wo, CU_TENSOR_MAP_DATA_TYPE_BFLOAT16, 3, d_in[2], gd, gs, bd, es, CU_TENSOR_MAP_INTERLEAVE_NONE, S128,
            CU_TENSOR_MAP_L2_PROMOTION_L2_128B, CU_TENSOR_MAP_FLOAT_OOB_FILL_NONE);
    }
    enc2(enc, &P.wg, d_in[4], FF, DM, 64, 64, S128);
    enc2(enc, &P.wu, d_in[5], FF, DM, 64, 64, S128);
    enc2(enc, &P.wd, d_in[6], DM, FF, 64, 128, S128);
    P.x = (const __nv_bfloat16*)d_in[0];
    P.p_wqkv = (const __nv_bfloat16*)d_in[1];
    P.p_wo = (const __nv_bfloat16*)d_in[2];
    P.p_wg = (const __nv_bfloat16*)d_in[4];
    P.p_wu = (const __nv_bfloat16*)d_in[5];
    P.p_wd = (const __nv_bfloat16*)d_in[6];
    P.use_smid = sms == NCTA ? 1 : 0;
    fused_layers_kernel<<<NCTA, NTHREADS, SM_TOTAL>>>(P);
}
```

```cpp
#include <cuda_runtime.h>
#include <cuda_bf16.h>
#include <cuda.h>
#include <stdint.h>

#define QPRE 5
#define GPRE 3
#define SEQ 2048
#define DM 448
#define FF 1792
#define NCTA 132
#define NTHREADS 640

#define SLOT 16384
#define NSLOT 14
#define SM_STG (13 * SLOT)
#define SM_MISC (NSLOT * SLOT)
#define SM_BAR SM_MISC
#define SM_DEC (SM_MISC + 328)
#define SM_QN (SM_MISC + 336)
#define SM_STATS (SM_MISC + 352)
#define SM_CSG (SM_STATS + 1024)
#define SM_CSQ (SM_CSG + 1024)
#define SM_TOTAL (SM_CSQ + 672)
#define B_F 0
#define B_E 14
#define B_ST 28
#define B_STG 29
#define B_RES 37
#define B_AI 39
#define B_FR 38
#define B_LOC 40
#define FULL(s) (sb + SM_BAR + (B_F + (s)) * 8)
#define EMPTY(s) (sb + SM_BAR + (B_E + (s)) * 8)
#define BAR(i) (sb + SM_BAR + (i) * 8)
#define PM_QKV 0x30ffu
#define PM_ATT 0x210cu
#define PM_WO 0xfffu
#define PM_GU 0x13ffu
#define PM_DN 0x1ce0u
#define Q1_SLOT(k) ((0xD7CB9A8u >> (4 * (k))) & 15)
#define DB_SLOT(j) ((0x87CBAu >> (4 * (j))) & 15)
#define NB_WG 1
#define NB_ORD0 5
#define NB_ORD1 6
#define NB_ALL 7
#define NB_PARK 8
#define NB_PAIR 13
#define NB_HST 11
#define NB_REL 9
#define NB_SKIP 7

__device__ __align__(1024) __nv_bfloat16 g_kv[2 * 16 * 16 * 2 * 128 * 32];
__device__ __align__(1024) __nv_bfloat16 g_o[2 * SEQ * 512];
__device__ __align__(1024) __nv_bfloat16 g_x[3 * SEQ * DM];
__device__ __align__(1024) __nv_bfloat16 g_h[2 * SEQ * FF];
__device__ __align__(128) float2 g_st[3 * 16 * 7 * 128];
__device__ __align__(128) float g_csgu[2 * FF];
__device__ __align__(128) float g_nrm[2 * 16 * 16 * 8 * 8];
#define FL_O(l, rb) ((rb) * 32 + (l))
#define FL_X(b, rb) ((rb) * 32 + 2 + (b))
#define FL_XS_OFF 3
#define FL_H(l, rb, t) ((rb) * 32 + 8 + (l) * 4 + (t))
#define FL_KV(l, rb, ns) (512 + (ns) * 32 + (l) * 16 + (rb))
#define FL_CSGU 768
__device__ __align__(128) unsigned g_flags[800];
__device__ unsigned g_epoch;
__device__ unsigned g_done;

struct Params {
    CUtensorMap x_in;
    CUtensorMap x_ld;
    CUtensorMap h_ld;
    CUtensorMap h_st;
    CUtensorMap o_ld;
    CUtensorMap wqkv64;
    CUtensorMap wo;
    CUtensorMap wg;
    CUtensorMap wu;
    CUtensorMap wd;
    __nv_bfloat16* out;
    const __nv_bfloat16* p_wqkv;
    const __nv_bfloat16* p_wo;
    const __nv_bfloat16* p_wg;
    const __nv_bfloat16* p_wu;
    const __nv_bfloat16* p_wd;
};

__device__ __forceinline__ uint32_t s2u(const void* p) { return (uint32_t)__cvta_generic_to_shared(p); }
__device__ __forceinline__ uint64_t mkdesc(uint32_t addr, uint32_t lbo, uint32_t sbo, uint32_t swz) {
    return (uint64_t)((addr & 0x3FFFF) >> 4) | ((uint64_t)(lbo >> 4) << 16) | ((uint64_t)(sbo >> 4) << 32) | ((uint64_t)swz << 62);
}
__device__ __forceinline__ void mbar_init(uint32_t b, int c) { asm volatile("mbarrier.init.shared::cta.b64 [%0], %1;" ::"r"(b), "r"(c)); }
__device__ __forceinline__ void mbar_expect(uint32_t b, uint32_t bytes) { asm volatile("mbarrier.arrive.expect_tx.shared::cta.b64 _, [%0], %1;" ::"r"(b), "r"(bytes) : "memory"); }
__device__ __forceinline__ void mbar_arrive(uint32_t b, uint32_t cnt) { asm volatile("mbarrier.arrive.shared::cta.b64 _, [%0], %1;" ::"r"(b), "r"(cnt) : "memory"); }
__device__ __forceinline__ void mbar_arrive_c(uint32_t b, uint32_t cnt) { asm volatile("mbarrier.arrive.shared::cluster.b64 _, [%0], %1;" ::"r"(b), "r"(cnt) : "memory"); }
#define PEER(a) ((a) ^ 0x1000000u)
__device__ __forceinline__ void mbar_wait(uint32_t b, uint32_t ph) {
    asm volatile(
        "{\n.reg .pred p;\n.reg .u32 n;\nmov.u32 n, 0;\n"
        "LW:\nmbarrier.try_wait.parity.shared::cta.b64 p, [%0], %1;\n@p bra LD;\n"
        "add.u32 n, n, 1;\nsetp.lt.u32 p, n, 4000000;\n@p bra LW;\ntrap;\nLD:\n}" ::"r"(b), "r"(ph) : "memory");
}
__device__ __forceinline__ void mbar_wait_long(uint32_t b, uint32_t ph) {
    asm volatile(
        "{\n.reg .pred p;\n.reg .u32 n;\nmov.u32 n, 0;\n"
        "LW:\nmbarrier.test_wait.parity.shared::cta.b64 p, [%0], %1;\n@p bra LD;\nnanosleep.u32 200;\n"
        "add.u32 n, n, 1;\nsetp.lt.u32 p, n, 4000000;\n@p bra LW;\ntrap;\nLD:\n}" ::"r"(b), "r"(ph) : "memory");
}
__device__ __forceinline__ void nb_sync(int id, int n) { asm volatile("bar.sync %0, %1;" ::"r"(id), "r"(n) : "memory"); }
__device__ __forceinline__ void nb_arrive(int id, int n) { asm volatile("bar.arrive %0, %1;" ::"r"(id), "r"(n) : "memory"); }
__device__ __forceinline__ void wg_fence() { asm volatile("wgmma.fence.sync.aligned;" ::: "memory"); }
__device__ __forceinline__ void wg_commit() { asm volatile("wgmma.commit_group.sync.aligned;" ::: "memory"); }
template <int N> __device__ __forceinline__ void wg_wait() { asm volatile("wgmma.wait_group.sync.aligned %0;" ::"n"(N) : "memory"); }
template <int N> __device__ __forceinline__ void fence_regs(float (&d)[N]) {
#pragma unroll
    for (int i = 0; i < N; i++) asm volatile("" : "+f"(d[i])::"memory");
}
template <int N> __device__ __forceinline__ void zero_regs(float (&d)[N]) {
#pragma unroll
    for (int i = 0; i < N; i++) d[i] = 0.f;
    fence_regs(d);
}
template <int N> __device__ __forceinline__ void fence_regs(uint32_t (&d)[N]) {
#pragma unroll
    for (int i = 0; i < N; i++) asm volatile("" : "+r"(d[i])::"memory");
}
__device__ __forceinline__ void fence_async_smem() { asm volatile("fence.proxy.async.shared::cta;" ::: "memory"); }
__device__ __forceinline__ void fence_async_global() { asm volatile("fence.proxy.async.global;" ::: "memory"); }
__device__ __forceinline__ void tma_ld2(uint32_t dst, const CUtensorMap* tm, int c0, int c1, uint32_t bar) {
    asm volatile("cp.async.bulk.tensor.2d.shared::cluster.global.mbarrier::complete_tx::bytes [%0], [%1, {%3, %4}], [%2];"
                 ::"r"(dst), "l"(tm), "r"(bar), "r"(c0), "r"(c1) : "memory");
}
__device__ __forceinline__ void tma_mc2(uint32_t dst, const CUtensorMap* tm, int c0, int c1, uint32_t bar) {
    asm volatile("cp.async.bulk.tensor.2d.shared::cluster.global.mbarrier::complete_tx::bytes.multicast::cluster [%0], [%1, {%3, %4}], [%2], %5;"
                 ::"r"(dst), "l"(tm), "r"(bar), "r"(c0), "r"(c1), "h"((uint16_t)3) : "memory");
}
__device__ __forceinline__ void tma_mc4(uint32_t dst, const CUtensorMap* tm, int c0, int c3, uint32_t bar) {
    asm volatile("cp.async.bulk.tensor.4d.shared::cluster.global.mbarrier::complete_tx::bytes.multicast::cluster [%0], [%1, {%3, %5, %5, %4}], [%2], %6;"
                 ::"r"(dst), "l"(tm), "r"(bar), "r"(c0), "r"(c3), "r"(0), "h"((uint16_t)3) : "memory");
}
__device__ __forceinline__ void tma_st2(const CUtensorMap* tm, int c0, int c1, uint32_t src) {
    asm volatile("cp.async.bulk.tensor.2d.global.shared::cta.bulk_group [%0, {%1, %2}], [%3];" ::"l"(tm), "r"(c0), "r"(c1), "r"(src) : "memory");
}
__device__ __forceinline__ void bulk_ld(uint32_t dst, const void* src, uint32_t bytes, uint32_t bar) {
    asm volatile("cp.async.bulk.shared::cluster.global.mbarrier::complete_tx::bytes [%0], [%1], %2, [%3];" ::"r"(dst), "l"(src), "r"(bytes), "r"(bar) : "memory");
}
__device__ __forceinline__ void bulk_st(void* dst, uint32_t src, uint32_t bytes) {
    asm volatile("cp.async.bulk.global.shared::cta.bulk_group [%0], [%1], %2;" ::"l"(dst), "r"(src), "r"(bytes) : "memory");
}
__device__ __forceinline__ void bulk_peer(uint32_t dst, uint32_t src, uint32_t bytes, uint32_t bar) {
    asm volatile("cp.async.bulk.shared::cluster.shared::cta.mbarrier::complete_tx::bytes [%0], [%1], %2, [%3];" ::"r"(dst), "r"(src), "r"(bytes), "r"(bar) : "memory");
}
__device__ __forceinline__ void bulk_commit() { asm volatile("cp.async.bulk.commit_group;" ::: "memory"); }
__device__ __forceinline__ void bulk_wait_all() { asm volatile("cp.async.bulk.wait_group 0;" ::: "memory"); }
__device__ __forceinline__ void bulk_wait_read() { asm volatile("cp.async.bulk.wait_group.read 0;" ::: "memory"); }
__device__ __forceinline__ void flag_release(int idx) {
    fence_async_global();
    asm volatile("red.release.gpu.global.add.u32 [%0], 1;" ::"l"(&g_flags[idx]) : "memory");
}
__device__ __forceinline__ unsigned flag_ld(int idx) {
    unsigned v;
    asm volatile("ld.relaxed.gpu.global.u32 %0, [%1];" : "=r"(v) : "l"(&g_flags[idx]) : "memory");
    return v;
}
__device__ __forceinline__ void fence_acq() { asm volatile("fence.acquire.gpu;" ::: "memory"); }
__device__ __forceinline__ bool elect() {
    uint32_t p;
    asm volatile("{\n.reg .pred P;\nelect.sync _|P, 0xffffffff;\nselp.u32 %0, 1, 0, P;\n}" : "=r"(p));
    return p != 0;
}
__device__ __forceinline__ float ex2(float x) { float y; asm("ex2.approx.ftz.f32 %0, %1;" : "=f"(y) : "f"(x)); return y; }
__device__ __forceinline__ float tanh_approx(float x) { float y; asm("tanh.approx.f32 %0, %1;" : "=f"(y) : "f"(x)); return y; }
__device__ __forceinline__ float rcp(float x) { float y; asm("rcp.approx.ftz.f32 %0, %1;" : "=f"(y) : "f"(x)); return y; }
__device__ __forceinline__ uint32_t packbf(float lo, float hi) { uint32_t y; asm("cvt.rn.bf16x2.f32 %0, %1, %2;" : "=r"(y) : "f"(hi), "f"(lo)); return y; }
__device__ __forceinline__ float bflo(uint32_t v) { return __uint_as_float(v << 16); }
__device__ __forceinline__ float bfhi(uint32_t v) { return __uint_as_float(v & 0xFFFF0000u); }
__device__ __forceinline__ void stg128(void* p, const uint4& v) {
    asm volatile("st.global.v4.b32 [%0], {%1,%2,%3,%4};" ::"l"(__cvta_generic_to_global(p)), "r"(v.x), "r"(v.y), "r"(v.z), "r"(v.w) : "memory");
}
__device__ __forceinline__ void stsm4(uint32_t a, uint32_t r0, uint32_t r1, uint32_t r2, uint32_t r3) {
    asm volatile("stmatrix.sync.aligned.m8n8.x4.shared.b16 [%0], {%1,%2,%3,%4};" ::"r"(a), "r"(r0), "r"(r1), "r"(r2), "r"(r3) : "memory");
}
__device__ __forceinline__ void ldsm4(uint32_t a, uint32_t& r0, uint32_t& r1, uint32_t& r2, uint32_t& r3) {
    asm volatile("ldmatrix.sync.aligned.m8n8.x4.shared.b16 {%0,%1,%2,%3}, [%4];" : "=r"(r0), "=r"(r1), "=r"(r2), "=r"(r3) : "r"(a) : "memory");
}

template <int TB> __device__ __forceinline__ void wgmma_rs_32(float (&d)[16], uint32_t a0, uint32_t a1, uint32_t a2, uint32_t a3, uint64_t db) {
    asm volatile("wgmma.mma_async.sync.aligned.m64n32k16.f32.bf16.bf16 {%0,%1,%2,%3,%4,%5,%6,%7,%8,%9,%10,%11,%12,%13,%14,%15}, {%16,%17,%18,%19}, %20, 1, 1, 1, %21;\n"
        : "+f"(d[0]), "+f"(d[1]), "+f"(d[2]), "+f"(d[3]), "+f"(d[4]), "+f"(d[5]), "+f"(d[6]), "+f"(d[7]),
        "+f"(d[8]), "+f"(d[9]), "+f"(d[10]), "+f"(d[11]), "+f"(d[12]), "+f"(d[13]), "+f"(d[14]), "+f"(d[15])
        : "r"(a0), "r"(a1), "r"(a2), "r"(a3), "l"(db), "n"(TB));
}
template <int TB> __device__ __forceinline__ void wgmma_ss_64(float (&d)[32], uint64_t da, uint64_t db) {
    asm volatile("wgmma.mma_async.sync.aligned.m64n64k16.f32.bf16.bf16 {%0,%1,%2,%3,%4,%5,%6,%7,%8,%9,%10,%11,%12,%13,%14,%15,%16,%17,%18,%19,%20,%21,%22,%23,%24,%25,%26,%27,%28,%29,%30,%31}, %32, %33, 1, 1, 1, 0, %34;\n"
        : "+f"(d[0]), "+f"(d[1]), "+f"(d[2]), "+f"(d[3]), "+f"(d[4]), "+f"(d[5]), "+f"(d[6]), "+f"(d[7]),
        "+f"(d[8]), "+f"(d[9]), "+f"(d[10]), "+f"(d[11]), "+f"(d[12]), "+f"(d[13]), "+f"(d[14]), "+f"(d[15]),
        "+f"(d[16]), "+f"(d[17]), "+f"(d[18]), "+f"(d[19]), "+f"(d[20]), "+f"(d[21]), "+f"(d[22]), "+f"(d[23]),
        "+f"(d[24]), "+f"(d[25]), "+f"(d[26]), "+f"(d[27]), "+f"(d[28]), "+f"(d[29]), "+f"(d[30]), "+f"(d[31])
        : "l"(da), "l"(db), "n"(TB));
}
template <int TB> __device__ __forceinline__ void wgmma_ssz_64(float (&d)[32], uint64_t da, uint64_t db) {
    asm volatile("wgmma.mma_async.sync.aligned.m64n64k16.f32.bf16.bf16 {%0,%1,%2,%3,%4,%5,%6,%7,%8,%9,%10,%11,%12,%13,%14,%15,%16,%17,%18,%19,%20,%21,%22,%23,%24,%25,%26,%27,%28,%29,%30,%31}, %32, %33, 0, 1, 1, 0, %34;\n"
        : "=f"(d[0]), "=f"(d[1]), "=f"(d[2]), "=f"(d[3]), "=f"(d[4]), "=f"(d[5]), "=f"(d[6]), "=f"(d[7]),
        "=f"(d[8]), "=f"(d[9]), "=f"(d[10]), "=f"(d[11]), "=f"(d[12]), "=f"(d[13]), "=f"(d[14]), "=f"(d[15]),
        "=f"(d[16]), "=f"(d[17]), "=f"(d[18]), "=f"(d[19]), "=f"(d[20]), "=f"(d[21]), "=f"(d[22]), "=f"(d[23]),
        "=f"(d[24]), "=f"(d[25]), "=f"(d[26]), "=f"(d[27]), "=f"(d[28]), "=f"(d[29]), "=f"(d[30]), "=f"(d[31])
        : "l"(da), "l"(db), "n"(TB));
}
template <int TB> __device__ __forceinline__ void wgmma_rs_64(float (&d)[32], uint32_t a0, uint32_t a1, uint32_t a2, uint32_t a3, uint64_t db) {
    asm volatile("wgmma.mma_async.sync.aligned.m64n64k16.f32.bf16.bf16 {%0,%1,%2,%3,%4,%5,%6,%7,%8,%9,%10,%11,%12,%13,%14,%15,%16,%17,%18,%19,%20,%21,%22,%23,%24,%25,%26,%27,%28,%29,%30,%31}, {%32,%33,%34,%35}, %36, 1, 1, 1, %37;\n"
        : "+f"(d[0]), "+f"(d[1]), "+f"(d[2]), "+f"(d[3]), "+f"(d[4]), "+f"(d[5]), "+f"(d[6]), "+f"(d[7]),
        "+f"(d[8]), "+f"(d[9]), "+f"(d[10]), "+f"(d[11]), "+f"(d[12]), "+f"(d[13]), "+f"(d[14]), "+f"(d[15]),
        "+f"(d[16]), "+f"(d[17]), "+f"(d[18]), "+f"(d[19]), "+f"(d[20]), "+f"(d[21]), "+f"(d[22]), "+f"(d[23]),
        "+f"(d[24]), "+f"(d[25]), "+f"(d[26]), "+f"(d[27]), "+f"(d[28]), "+f"(d[29]), "+f"(d[30]), "+f"(d[31])
        : "r"(a0), "r"(a1), "r"(a2), "r"(a3), "l"(db), "n"(TB));
}
template <int TB> __device__ __forceinline__ void wgmma_rsz_64(float (&d)[32], uint32_t a0, uint32_t a1, uint32_t a2, uint32_t a3, uint64_t db) {
    asm volatile("wgmma.mma_async.sync.aligned.m64n64k16.f32.bf16.bf16 {%0,%1,%2,%3,%4,%5,%6,%7,%8,%9,%10,%11,%12,%13,%14,%15,%16,%17,%18,%19,%20,%21,%22,%23,%24,%25,%26,%27,%28,%29,%30,%31}, {%32,%33,%34,%35}, %36, 0, 1, 1, %37;\n"
        : "=f"(d[0]), "=f"(d[1]), "=f"(d[2]), "=f"(d[3]), "=f"(d[4]), "=f"(d[5]), "=f"(d[6]), "=f"(d[7]),
        "=f"(d[8]), "=f"(d[9]), "=f"(d[10]), "=f"(d[11]), "=f"(d[12]), "=f"(d[13]), "=f"(d[14]), "=f"(d[15]),
        "=f"(d[16]), "=f"(d[17]), "=f"(d[18]), "=f"(d[19]), "=f"(d[20]), "=f"(d[21]), "=f"(d[22]), "=f"(d[23]),
        "=f"(d[24]), "=f"(d[25]), "=f"(d[26]), "=f"(d[27]), "=f"(d[28]), "=f"(d[29]), "=f"(d[30]), "=f"(d[31])
        : "r"(a0), "r"(a1), "r"(a2), "r"(a3), "l"(db), "n"(TB));
}
template <int TB> __device__ __forceinline__ void wgmma_ss_128(float (&d)[64], uint64_t da, uint64_t db) {
    asm volatile("wgmma.mma_async.sync.aligned.m64n128k16.f32.bf16.bf16 {%0,%1,%2,%3,%4,%5,%6,%7,%8,%9,%10,%11,%12,%13,%14,%15,%16,%17,%18,%19,%20,%21,%22,%23,%24,%25,%26,%27,%28,%29,%30,%31,%32,%33,%34,%35,%36,%37,%38,%39,%40,%41,%42,%43,%44,%45,%46,%47,%48,%49,%50,%51,%52,%53,%54,%55,%56,%57,%58,%59,%60,%61,%62,%63}, %64, %65, 1, 1, 1, 0, %66;\n"
        : "+f"(d[0]), "+f"(d[1]), "+f"(d[2]), "+f"(d[3]), "+f"(d[4]), "+f"(d[5]), "+f"(d[6]), "+f"(d[7]),
        "+f"(d[8]), "+f"(d[9]), "+f"(d[10]), "+f"(d[11]), "+f"(d[12]), "+f"(d[13]), "+f"(d[14]), "+f"(d[15]),
        "+f"(d[16]), "+f"(d[17]), "+f"(d[18]), "+f"(d[19]), "+f"(d[20]), "+f"(d[21]), "+f"(d[22]), "+f"(d[23]),
        "+f"(d[24]), "+f"(d[25]), "+f"(d[26]), "+f"(d[27]), "+f"(d[28]), "+f"(d[29]), "+f"(d[30]), "+f"(d[31]),
        "+f"(d[32]), "+f"(d[33]), "+f"(d[34]), "+f"(d[35]), "+f"(d[36]), "+f"(d[37]), "+f"(d[38]), "+f"(d[39]),
        "+f"(d[40]), "+f"(d[41]), "+f"(d[42]), "+f"(d[43]), "+f"(d[44]), "+f"(d[45]), "+f"(d[46]), "+f"(d[47]),
        "+f"(d[48]), "+f"(d[49]), "+f"(d[50]), "+f"(d[51]), "+f"(d[52]), "+f"(d[53]), "+f"(d[54]), "+f"(d[55]),
        "+f"(d[56]), "+f"(d[57]), "+f"(d[58]), "+f"(d[59]), "+f"(d[60]), "+f"(d[61]), "+f"(d[62]), "+f"(d[63])
        : "l"(da), "l"(db), "n"(TB));
}
template <int TB> __device__ __forceinline__ void wgmma_ssz_128(float (&d)[64], uint64_t da, uint64_t db) {
    asm volatile("wgmma.mma_async.sync.aligned.m64n128k16.f32.bf16.bf16 {%0,%1,%2,%3,%4,%5,%6,%7,%8,%9,%10,%11,%12,%13,%14,%15,%16,%17,%18,%19,%20,%21,%22,%23,%24,%25,%26,%27,%28,%29,%30,%31,%32,%33,%34,%35,%36,%37,%38,%39,%40,%41,%42,%43,%44,%45,%46,%47,%48,%49,%50,%51,%52,%53,%54,%55,%56,%57,%58,%59,%60,%61,%62,%63}, %64, %65, 0, 1, 1, 0, %66;\n"
        : "=f"(d[0]), "=f"(d[1]), "=f"(d[2]), "=f"(d[3]), "=f"(d[4]), "=f"(d[5]), "=f"(d[6]), "=f"(d[7]),
        "=f"(d[8]), "=f"(d[9]), "=f"(d[10]), "=f"(d[11]), "=f"(d[12]), "=f"(d[13]), "=f"(d[14]), "=f"(d[15]),
        "=f"(d[16]), "=f"(d[17]), "=f"(d[18]), "=f"(d[19]), "=f"(d[20]), "=f"(d[21]), "=f"(d[22]), "=f"(d[23]),
        "=f"(d[24]), "=f"(d[25]), "=f"(d[26]), "=f"(d[27]), "=f"(d[28]), "=f"(d[29]), "=f"(d[30]), "=f"(d[31]),
        "=f"(d[32]), "=f"(d[33]), "=f"(d[34]), "=f"(d[35]), "=f"(d[36]), "=f"(d[37]), "=f"(d[38]), "=f"(d[39]),
        "=f"(d[40]), "=f"(d[41]), "=f"(d[42]), "=f"(d[43]), "=f"(d[44]), "=f"(d[45]), "=f"(d[46]), "=f"(d[47]),
        "=f"(d[48]), "=f"(d[49]), "=f"(d[50]), "=f"(d[51]), "=f"(d[52]), "=f"(d[53]), "=f"(d[54]), "=f"(d[55]),
        "=f"(d[56]), "=f"(d[57]), "=f"(d[58]), "=f"(d[59]), "=f"(d[60]), "=f"(d[61]), "=f"(d[62]), "=f"(d[63])
        : "l"(da), "l"(db), "n"(TB));
}
template <int TB> __device__ __forceinline__ void wgmma_ss_120(float (&d)[60], uint64_t da, uint64_t db) {
    asm volatile("wgmma.mma_async.sync.aligned.m64n120k16.f32.bf16.bf16 {%0,%1,%2,%3,%4,%5,%6,%7,%8,%9,%10,%11,%12,%13,%14,%15,%16,%17,%18,%19,%20,%21,%22,%23,%24,%25,%26,%27,%28,%29,%30,%31,%32,%33,%34,%35,%36,%37,%38,%39,%40,%41,%42,%43,%44,%45,%46,%47,%48,%49,%50,%51,%52,%53,%54,%55,%56,%57,%58,%59}, %60, %61, 1, 1, 1, 0, %62;\n"
        : "+f"(d[0]), "+f"(d[1]), "+f"(d[2]), "+f"(d[3]), "+f"(d[4]), "+f"(d[5]), "+f"(d[6]), "+f"(d[7]),
        "+f"(d[8]), "+f"(d[9]), "+f"(d[10]), "+f"(d[11]), "+f"(d[12]), "+f"(d[13]), "+f"(d[14]), "+f"(d[15]),
        "+f"(d[16]), "+f"(d[17]), "+f"(d[18]), "+f"(d[19]), "+f"(d[20]), "+f"(d[21]), "+f"(d[22]), "+f"(d[23]),
        "+f"(d[24]), "+f"(d[25]), "+f"(d[26]), "+f"(d[27]), "+f"(d[28]), "+f"(d[29]), "+f"(d[30]), "+f"(d[31]),
        "+f"(d[32]), "+f"(d[33]), "+f"(d[34]), "+f"(d[35]), "+f"(d[36]), "+f"(d[37]), "+f"(d[38]), "+f"(d[39]),
        "+f"(d[40]), "+f"(d[41]), "+f"(d[42]), "+f"(d[43]), "+f"(d[44]), "+f"(d[45]), "+f"(d[46]), "+f"(d[47]),
        "+f"(d[48]), "+f"(d[49]), "+f"(d[50]), "+f"(d[51]), "+f"(d[52]), "+f"(d[53]), "+f"(d[54]), "+f"(d[55]),
        "+f"(d[56]), "+f"(d[57]), "+f"(d[58]), "+f"(d[59])
        : "l"(da), "l"(db), "n"(TB));
}
template <int TB> __device__ __forceinline__ void wgmma_ssz_120(float (&d)[60], uint64_t da, uint64_t db) {
    asm volatile("wgmma.mma_async.sync.aligned.m64n120k16.f32.bf16.bf16 {%0,%1,%2,%3,%4,%5,%6,%7,%8,%9,%10,%11,%12,%13,%14,%15,%16,%17,%18,%19,%20,%21,%22,%23,%24,%25,%26,%27,%28,%29,%30,%31,%32,%33,%34,%35,%36,%37,%38,%39,%40,%41,%42,%43,%44,%45,%46,%47,%48,%49,%50,%51,%52,%53,%54,%55,%56,%57,%58,%59}, %60, %61, 0, 1, 1, 0, %62;\n"
        : "=f"(d[0]), "=f"(d[1]), "=f"(d[2]), "=f"(d[3]), "=f"(d[4]), "=f"(d[5]), "=f"(d[6]), "=f"(d[7]),
        "=f"(d[8]), "=f"(d[9]), "=f"(d[10]), "=f"(d[11]), "=f"(d[12]), "=f"(d[13]), "=f"(d[14]), "=f"(d[15]),
        "=f"(d[16]), "=f"(d[17]), "=f"(d[18]), "=f"(d[19]), "=f"(d[20]), "=f"(d[21]), "=f"(d[22]), "=f"(d[23]),
        "=f"(d[24]), "=f"(d[25]), "=f"(d[26]), "=f"(d[27]), "=f"(d[28]), "=f"(d[29]), "=f"(d[30]), "=f"(d[31]),
        "=f"(d[32]), "=f"(d[33]), "=f"(d[34]), "=f"(d[35]), "=f"(d[36]), "=f"(d[37]), "=f"(d[38]), "=f"(d[39]),
        "=f"(d[40]), "=f"(d[41]), "=f"(d[42]), "=f"(d[43]), "=f"(d[44]), "=f"(d[45]), "=f"(d[46]), "=f"(d[47]),
        "=f"(d[48]), "=f"(d[49]), "=f"(d[50]), "=f"(d[51]), "=f"(d[52]), "=f"(d[53]), "=f"(d[54]), "=f"(d[55]),
        "=f"(d[56]), "=f"(d[57]), "=f"(d[58]), "=f"(d[59])
        : "l"(da), "l"(db), "n"(TB));
}
template <int TB> __device__ __forceinline__ void wgmma_ss_56(float (&d)[28], uint64_t da, uint64_t db) {
    asm volatile("wgmma.mma_async.sync.aligned.m64n56k16.f32.bf16.bf16 {%0,%1,%2,%3,%4,%5,%6,%7,%8,%9,%10,%11,%12,%13,%14,%15,%16,%17,%18,%19,%20,%21,%22,%23,%24,%25,%26,%27}, %28, %29, 1, 1, 1, 0, %30;\n"
        : "+f"(d[0]), "+f"(d[1]), "+f"(d[2]), "+f"(d[3]), "+f"(d[4]), "+f"(d[5]), "+f"(d[6]), "+f"(d[7]),
        "+f"(d[8]), "+f"(d[9]), "+f"(d[10]), "+f"(d[11]), "+f"(d[12]), "+f"(d[13]), "+f"(d[14]), "+f"(d[15]),
        "+f"(d[16]), "+f"(d[17]), "+f"(d[18]), "+f"(d[19]), "+f"(d[20]), "+f"(d[21]), "+f"(d[22]), "+f"(d[23]),
        "+f"(d[24]), "+f"(d[25]), "+f"(d[26]), "+f"(d[27])
        : "l"(da), "l"(db), "n"(TB));
}
template <int TB> __device__ __forceinline__ void wgmma_ssz_56(float (&d)[28], uint64_t da, uint64_t db) {
    asm volatile("wgmma.mma_async.sync.aligned.m64n56k16.f32.bf16.bf16 {%0,%1,%2,%3,%4,%5,%6,%7,%8,%9,%10,%11,%12,%13,%14,%15,%16,%17,%18,%19,%20,%21,%22,%23,%24,%25,%26,%27}, %28, %29, 0, 1, 1, 0, %30;\n"
        : "=f"(d[0]), "=f"(d[1]), "=f"(d[2]), "=f"(d[3]), "=f"(d[4]), "=f"(d[5]), "=f"(d[6]), "=f"(d[7]),
        "=f"(d[8]), "=f"(d[9]), "=f"(d[10]), "=f"(d[11]), "=f"(d[12]), "=f"(d[13]), "=f"(d[14]), "=f"(d[15]),
        "=f"(d[16]), "=f"(d[17]), "=f"(d[18]), "=f"(d[19]), "=f"(d[20]), "=f"(d[21]), "=f"(d[22]), "=f"(d[23]),
        "=f"(d[24]), "=f"(d[25]), "=f"(d[26]), "=f"(d[27])
        : "l"(da), "l"(db), "n"(TB));
}

#define POLY_MASK 0xDAu
#define K_MUFU_BITS 0x3AA83F19u
#define K_POLY_BITS 0x000043BFu
#define Q_PAD_BITS 0x3F803F80u
#define V_PAD_BITS 0x00003F80u
#define SAFE_BOUND2 (60.0f * 60.0f)

__device__ __forceinline__ uint32_t exp2_pair(float t0, float t1, uint32_t cneg1) {
    uint32_t w = __byte_perm(__float_as_uint(t0), __float_as_uint(t1), 0x6521);
    uint32_t u, r;
    asm("lop3.b32 %0, %1, 0x007F007F, %2, 0xEA;" : "=r"(u) : "r"(w), "r"(cneg1));
    asm("fma.rn.bf16x2 %0, %1, %1, %2;" : "=r"(r) : "r"(u), "r"(0x40034003u));
    return w - u + r;
}
__device__ __forceinline__ void softmax_fast(float (&s)[32], uint32_t (&p)[16], uint32_t cneg1) {
#pragma unroll
    for (int j = 0; j < 8; j++) {
        if ((POLY_MASK >> j) & 1) {
            p[2 * j] = exp2_pair(s[4 * j], s[4 * j + 1], cneg1);
            p[2 * j + 1] = exp2_pair(s[4 * j + 2], s[4 * j + 3], cneg1);
        } else {
            p[2 * j] = packbf(ex2(s[4 * j]), ex2(s[4 * j + 1]));
            p[2 * j + 1] = packbf(ex2(s[4 * j + 2]), ex2(s[4 * j + 3]));
        }
    }
}

__device__ __forceinline__ void helper_cta(const Params& P, int e, char* sm) {
    const int t = threadIdx.x;
    __nanosleep(4000);
    if (t == 0) {
        const char* wo = (const char*)P.p_wo + e * (DM * DM * 2 / 4);
        for (int o = 0; o < DM * DM * 2 / 4; o += 14336) asm volatile("cp.async.bulk.prefetch.L2.global [%0], %1;" ::"l"(wo + o), "r"(14336));
    }
    float* red = (float*)sm;
    if (t < 448) {
        int c = t % 112, rg = t / 112;
        const __nv_bfloat16* W = (c < 56 ? P.p_wg : P.p_wu) + e * 448 + (c < 56 ? c : c - 56) * 8;
        float a[8];
#pragma unroll
        for (int i = 0; i < 8; i++) a[i] = 0.f;
#pragma unroll 14
        for (int r = rg; r < DM; r += 4) {
            uint4 v = __ldg((const uint4*)(W + (size_t)r * FF));
            a[0] += bflo(v.x); a[1] += bfhi(v.x); a[2] += bflo(v.y); a[3] += bfhi(v.y);
            a[4] += bflo(v.z); a[5] += bfhi(v.z); a[6] += bflo(v.w); a[7] += bfhi(v.w);
        }
#pragma unroll
        for (int i = 0; i < 8; i++) red[rg * 896 + c * 8 + i] = a[i];
    }
    nb_sync(NB_ALL, 512);
    for (int c = t; c < 896; c += 512) {
        float s = red[c] + red[896 + c] + red[2 * 896 + c] + red[3 * 896 + c];
        const int f = e * 448 + (c < 448 ? c : c - 448);
        g_csgu[(f >> 1) * 4 + (c < 448 ? 0 : 2) + (f & 1)] = s;
    }
    nb_sync(NB_ALL, 512);
    if (t == 0) {
        flag_release(FL_CSGU);
        const char* wd = (const char*)P.p_wd + e * (FF * DM * 2 / 4);
        for (int o = 0; o < FF * DM * 2 / 4; o += 14336) asm volatile("cp.async.bulk.prefetch.L2.global [%0], %1;" ::"l"(wd + o), "r"(14336));
    }
}

#define ARM(S) { mbar_wait(EMPTY(S), ((pm >> (S)) ^ 1) & 1); if (elect()) mbar_expect(FULL(S), SLOT); }
#define FIRE(S, TM, C0, C1) tma_ld2(sb + (S) * SLOT, TM, C0, C1, FULL(S));
#define ITEM(S, U, BYTES, ISSUE)                                       \
    {                                                                  \
        const uint32_t s_ = (S);                                       \
        mbar_wait(EMPTY(s_), ((pm >> s_) ^ (U) ^ 1) & 1);              \
        const uint32_t fb = FULL(s_), dst = sb + s_ * SLOT;            \
        if (elect()) { mbar_expect(fb, BYTES); ISSUE; }                \
    }

__device__ __forceinline__ void producer_w(const Params& P, uint32_t sb, int vid) {
    const int ns = vid & 7, rank = (vid >> 3) & 1;
    const bool act = ns < 7;
    uint32_t pm = 0;
#pragma unroll 1
    for (int l = 0; l < 2; l++) {
        if (l == 1) {
#pragma unroll
            for (int k = 0; k < 7; k++) {
                if (k == QPRE) mbar_wait(BAR(B_AI), 0);
                ITEM(Q1_SLOT(k), 0, SLOT, tma_mc2(dst + rank * 8192, &P.wqkv64, (rank + 1) * DM + ns * 56, k * 64, fb))
            }
        }
#pragma unroll
        for (int k = 0; k < 4; k++)
            ITEM(Q1_SLOT(k), 1, k < 3 ? SLOT : 8192, if (k < 3 || rank == 0) tma_mc2(dst + rank * 8192, &P.wqkv64, ns * 56, k * 128 + rank * 64, fb))
        pm ^= PM_QKV;
        mbar_wait_long(FULL(0), pm & 1);
        pm ^= PM_ATT;
        if (act) {
#pragma unroll
            for (int k = 0; k < 4; k++) ITEM(k < 3 ? 9 + k : 7, 0, SLOT, tma_mc4(dst + rank * 8192, &P.wo, ns * 64, 2 * k + rank, fb))
            pm ^= PM_WO;
        }
        const CUtensorMap* wgu = rank ? &P.wu : &P.wg;
#pragma unroll
        for (int k = 0; k < 28; k++) {
            if (k == 1) { nb_sync(NB_PARK, 224); if (act) mbar_wait(BAR(B_FR), 0); }
            if (k == GPRE) mbar_wait(BAR(B_AI), 1);
            ITEM(7 + (k + 5) % 6, k / 6, SLOT, tma_mc2(dst + rank * 8192, wgu, (k < 21 ? 8 * (k / 7) + ns : 24 + (ns >> 1)) * 64, (k % 7) * 64, fb))
        }
        pm ^= PM_GU;
        if (act) {
#pragma unroll
            for (int k = 0; k < 14; k++)
                ITEM(DB_SLOT(k % 5), k / 5, SLOT, tma_mc2(dst + rank * 8192, &P.wd, ns * 64, k * 128 + rank * 64, fb))
            pm ^= PM_DN;
        }
    }
}

__device__ __forceinline__ void wait_flags(int idx, unsigned target) {
    unsigned n = 0;
    while (!__all_sync(0xffffffffu, (int)(flag_ld(idx) - target) >= 0)) { if (++n > 4000000u) __trap(); }
    fence_acq();
    fence_async_global();
}

__device__ __forceinline__ void producer_a(const Params& P, uint32_t sb, char* sm, const int vid, const unsigned ep) {
    uint32_t pm = 0;
    const int g = vid >> 4, rb = vid >> 3, ns = vid & 7, h = 2 * ns + (rb & 1);
    const bool act = ns < 7;
#pragma unroll 1
    for (int l = 0; l < 2; l++) {
        int lane;
        asm volatile("mov.u32 %0, %%laneid;" : "=r"(lane));
        const CUtensorMap* xm = l == 0 ? &P.x_in : &P.x_ld;
        const int xr = (l == 0 ? 0 : SEQ) + rb * 128;
        if (l == 0) {
            if (elect()) mbar_arrive(BAR(B_AI), 1);
        } else {
#pragma unroll
            for (int k = 5; k < 12; k++) ARM(k % 7)
            wait_flags(FL_X(1, rb), 7 * ep);
            if (elect()) {
#pragma unroll
                for (int k = 0; k < 7; k++) { FIRE(k, xm, k * 64, xr) if (k == 0) mbar_arrive(BAR(B_AI), 1); }
            }
        }
        pm ^= PM_QKV;
        {
            const __nv_bfloat16* kvb = g_kv + (size_t)(l * 16 + h) * 16 * 8192;
            const uint32_t pe = (lane & 1) ? 0x1000000u : 0u;
            mbar_wait(FULL(13), ((pm >> 13) ^ 1) & 1);
            ITEM(13, 0, SLOT + 32, (void)dst)
            ITEM(8, 0, 8192, (void)dst)
#pragma unroll
            for (int k = 0; k < 4; k++) {
                if (!(k & 1)) wait_flags(FL_KV(l, (2 * g + 2 + k + (lane & 1)) & 15, ns), 2 * ep);
                ITEM(k, 0, SLOT, bulk_ld(dst, kvb + (size_t)((2 * g + 2 + k) & 15) * 8192, SLOT, fb))
            }
            wait_flags(FL_KV(l, lane & 15, ns), 2 * ep);
            mbar_wait(FULL(13), (pm >> 13) & 1);
            mbar_wait(FULL(8), (pm >> 8) & 1);
            if (lane < 2) mbar_arrive_c(EMPTY(7) ^ pe, 8);
            const float* np = &g_nrm[((l * 16 + h) * 128 + lane) * 8];
            const unsigned kb = __reduce_max_sync(0xffffffffu, __float_as_uint(fmaxf(fmaxf(__ldcg(np), __ldcg(np + 256)), fmaxf(__ldcg(np + 512), __ldcg(np + 768)))));
            int kend = 14;
#pragma unroll 1
            for (int k = 4; k < kend; k++) {
                mbar_wait_long(EMPTY(k & 3), ((pm >> (k & 3)) ^ (k >> 2) ^ 1) & 1);
                if (k == 4) {
                    if (lane < 2) mbar_arrive_c(EMPTY(12) ^ pe, 8);
                    const bool redo = !(__uint_as_float(kb) * *(volatile float*)(sm + SM_QN + l * 4) <= SAFE_BOUND2);
                    *(volatile int*)(sm + SM_DEC) = redo ? 1 : 0;
                    kend = redo ? 30 : 14;
                    if (act && elect()) { mbar_expect(BAR(B_RES), SLOT); tma_ld2(sb + SM_STG, xm, ns * 64, xr, BAR(B_RES)); }
                }
                if (elect()) { mbar_expect(FULL(k & 3), SLOT); bulk_ld(sb + (k & 3) * SLOT, kvb + (size_t)((2 * g + 2 + k) & 15) * 8192, SLOT, FULL(k & 3)); }
            }
            pm ^= PM_ATT;
        }
        mbar_wait_long(EMPTY(3), ((pm >> 3) ^ 1) & 1);
        if (act) {
            ARM(4) ARM(5) ARM(6) ARM(2) ARM(3) ARM(0) ARM(1)
            wait_flags(FL_O(l, rb), 32 * ep);
            if (elect()) {
#pragma unroll
                for (int k = 0; k < 7; k++) FIRE(k, &P.o_ld, k * 64, l * SEQ + rb * 128)
            }
            ITEM(8, 0, SLOT, tma_ld2(dst, &P.o_ld, 7 * 64, l * SEQ + rb * 128, fb))
            pm ^= PM_WO;
        }
#pragma unroll
        for (int k = 0; k < 7; k++) ARM(k)
        wait_flags(FL_X(2 * l, rb), 7 * ep);
        if (elect()) {
#pragma unroll
            for (int k = 0; k < 7; k++) { FIRE(k, &P.x_ld, k * 64, 2 * l * SEQ + rb * 128) if (k == 0) mbar_arrive(BAR(B_AI), 1); }
        }
        pm ^= PM_GU;
        if (act) {
            const int fh = FL_H(l, rb, 0);
            mbar_wait_long(BAR(B_STG + 1), l);
            unsigned fv = 0;
#pragma unroll
            for (int k = 0; k < 28; k++) {
                if ((k & 7) == 0) {
                    if (k == 0 || !__all_sync(0xffffffffu, (int)(fv - (k < 24 ? 16 : 8) * ep) >= 0)) wait_flags(fh + k / 8, (k < 24 ? 16 : 8) * ep);
                    else { fence_acq(); fence_async_global(); }
                }
                if (k == 18) {
                    mbar_wait(BAR(B_STG + 2), l); mbar_wait(BAR(B_STG + 6), l);
                    if (elect()) { mbar_expect(BAR(B_RES), SLOT); tma_ld2(sb + SM_STG, &P.x_ld, ns * 64, 2 * l * SEQ + rb * 128, BAR(B_RES)); }
                }
                ITEM(k < 7 ? k : (((k + 1) & 7) < 7 ? ((k + 1) & 7) : 9), k < 7 ? 0 : (((k + 1) & 7) < 7 ? (k + 1) >> 3 : ((k + 1) >> 3) - 1), SLOT, tma_ld2(dst, &P.h_ld, k * 64, l * SEQ + rb * 128, fb))
                if ((k & 7) == 5 && k < 24) fv = flag_ld(fh + k / 8 + 1);
            }
            pm ^= PM_DN;
        }
    }
}

__device__ __forceinline__ float2 combine_stats(const float2* p) {
    float2 v[7];
#pragma unroll
    for (int i = 0; i < 7; i++) v[i] = __ldcg(p + i * 128);
    float mean = 0.f, m2 = 0.f, e = 0.f;
#pragma unroll
    for (int i = 0; i < 7; i++) { mean += v[i].x; m2 += v[i].y; }
    mean *= 1.f / 7.f;
#pragma unroll
    for (int i = 0; i < 7; i++) e = fmaf(v[i].x - mean, v[i].x - mean, e);
    return make_float2(mean, rsqrtf(fmaf(64.f, e, m2) * (1.f / DM) + 1e-5f));
}

__device__ __forceinline__ void service_warps(const Params& P, uint32_t sb, char* sm, const int vid, const unsigned ep, const int rh) {
    float2* s_stats = (float2*)(sm + SM_STATS);
    const int rb = vid >> 3, ns = vid & 7;
#pragma unroll 1
    for (int b = -1; b < 3; b++) {
        int lane;
        asm volatile("mov.u32 %0, %%laneid;" : "=r"(lane));
        const int l = (b + 1) >> 1;
        if (b >= 0) {
            if (b != 1) nb_sync(NB_PARK, 224);
            if (b == 0) wait_flags(FL_CSGU, 4 * ep);
            if (b != 1) ((float4*)(sm + SM_CSG))[rh * 32 + lane] = __ldcg((const float4*)g_csgu + (8 * rh + ns) * 32 + lane);
            wait_flags(FL_X(b, rb) + FL_XS_OFF, 7 * ep);
#pragma unroll 1
            for (int r = rh * 64 + lane; r < rh * 64 + 64; r += 32) s_stats[r] = combine_stats(&g_st[(b * 16 + rb) * 896 + r]);
            mbar_arrive(BAR(B_ST), 4);
        }
        if (b & 1) {
            const uint32_t ev = ((rb & 1) ? 7 : 12) * SLOT + rh * 4096, od = ((rb & 1) ? 12 : 7) * SLOT + rh * 4096;
            nb_sync(NB_HST + rh, 160);
            if (lane == 0) {
                mbar_arrive(BAR(B_LOC), 1);
#pragma unroll
                for (int i = 0; i < 4; i++)
                    bulk_st(g_kv + ((size_t)((l * 16 + 2 * ns + (i >> 1)) * 16 + rb) * 2 + (i & 1)) * 4096 + rh * 2048, sb + ((i >> 1) ? od : ev) + (i & 1) * 8192, 4096);
                bulk_commit();
                bulk_wait_all();
            }
            __syncwarp();
            if (lane < 4) mbar_arrive_c(EMPTY(lane < 2 ? 12 : 7) ^ ((lane & 1) ? 0x1000000u : 0u), 4);
            if (lane == 0) {
                flag_release(FL_KV(l, rb, ns));
                mbar_wait(EMPTY(13), 0);
                bulk_peer(PEER(sb + 13 * SLOT + rh * 4096), sb + 7 * SLOT + rh * 4096, 4096, PEER(FULL(13)));
                bulk_peer(PEER(sb + 13 * SLOT + 8192 + rh * 4096), sb + 7 * SLOT + 8192 + rh * 4096, 4096, PEER(FULL(13)));
            }
            __syncwarp();
        } else {
            const float4 nx = __ldcg((const float4*)g_csgu + (rh ? 24 + (ns >> 1) : 16 + ns) * 32 + lane);
#pragma unroll 1
            for (int u = 0; u < 3; u++) {
                nb_sync(NB_HST + rh, 160);
                if (lane == 0) {
                    tma_st2(&P.h_st, (8 * u + ns) * 64, (b >> 1) * SEQ + rb * 128 + rh * 64, sb + SM_STG + rh * 8192);
                    bulk_commit(); bulk_wait_read();
                    mbar_arrive(BAR(B_STG + rh * 4 + u), 1);
                    if (u == 2 && ns == 7) { mbar_arrive(EMPTY(13), 8); mbar_arrive_c(PEER(EMPTY(13)), 8); }
                }
                if (u == rh) {
                    mbar_wait(BAR(B_STG + (rh ^ 1) * 4 + u), b >> 1);
                    ((float4*)(sm + SM_CSG))[rh * 32 + lane] = nx;
                    __syncwarp();
                    if (lane == 0) mbar_arrive(BAR(B_STG + rh * 4 + 3), 1);
                }
                if (lane == 0) {
                    bulk_wait_all();
                    flag_release(FL_H(b >> 1, rb, u));
                }
                __syncwarp();
            }
        }
    }
}

template <int N> __device__ __forceinline__ void wgmma_qkv(float (&d)[N / 2], uint64_t da, uint64_t db);
template <int N> __device__ __forceinline__ void wgmma_qkvz(float (&d)[N / 2], uint64_t da, uint64_t db);
template <> __device__ __forceinline__ void wgmma_qkvz<120>(float (&d)[60], uint64_t da, uint64_t db) { wgmma_ssz_120<1>(d, da, db); }
template <> __device__ __forceinline__ void wgmma_qkvz<56>(float (&d)[28], uint64_t da, uint64_t db) { wgmma_ssz_56<1>(d, da, db); }
template <> __device__ __forceinline__ void wgmma_qkv<120>(float (&d)[60], uint64_t da, uint64_t db) { wgmma_ss_120<1>(d, da, db); }
template <> __device__ __forceinline__ void wgmma_qkv<56>(float (&d)[28], uint64_t da, uint64_t db) { wgmma_ss_56<1>(d, da, db); }

__device__ __forceinline__ void hmma(float (&d)[4], uint32_t a0, uint32_t a1, uint32_t a2, uint32_t a3, uint32_t b0, uint32_t b1) {
    asm volatile("mma.sync.aligned.m16n8k16.row.col.f32.bf16.bf16.f32 {%0,%1,%2,%3}, {%4,%5,%6,%7}, {%8,%9}, {%0,%1,%2,%3};"
                 : "+f"(d[0]), "+f"(d[1]), "+f"(d[2]), "+f"(d[3]) : "r"(a0), "r"(a1), "r"(a2), "r"(a3), "r"(b0), "r"(b1));
}
__device__ __forceinline__ void colsum64(float (&d)[2][4], uint32_t tile, int blk, int lane) {
    uint32_t a[4][4];
#pragma unroll
    for (int i = 0; i < 4; i++)
        asm volatile("ldmatrix.sync.aligned.m8n8.x4.trans.shared.b16 {%0,%1,%2,%3}, [%4];" : "=r"(a[i][0]), "=r"(a[i][1]), "=r"(a[i][2]), "=r"(a[i][3])
                     : "r"(tile + (i * 16 + (lane >> 4) * 8 + (lane & 7)) * 128 + (((2 * blk + ((lane >> 3) & 1)) ^ (lane & 7)) << 4)) : "memory");
#pragma unroll
    for (int i = 0; i < 4; i++) hmma(d[i & 1], a[i][0], a[i][1], a[i][2], a[i][3], Q_PAD_BITS, Q_PAD_BITS);
}
__device__ __forceinline__ void first_layer_rows(uint32_t sb, char* sm, int w8, int lane) {
    float g0[2][4] = {}, g1[2][4] = {};
    const int r = w8 * 16 + (lane & 15);
#pragma unroll 1
    for (int kb = 0; kb < 7; kb++) {
        mbar_wait(FULL(kb), 0);
        uint32_t a[4][4];
#pragma unroll
        for (int k = 0; k < 4; k++) ldsm4(sb + kb * SLOT + r * 128 + (((2 * k + (lane >> 4)) ^ (r & 7)) << 4), a[k][0], a[k][1], a[k][2], a[k][3]);
#pragma unroll
        for (int k = 0; k < 4; k++) {
            hmma(g0[k & 1], a[k][0], Q_PAD_BITS, a[k][2], Q_PAD_BITS, a[k][0], a[k][2]);
            hmma(g1[k & 1], a[k][1], Q_PAD_BITS, a[k][3], Q_PAD_BITS, a[k][1], a[k][3]);
        }
    }
    if ((lane & 3) == (lane >> 3)) {
        const bool hi = (lane >> 2) & 1;
        const float m0 = (hi ? g0[0][3] + g0[1][3] : g0[0][2] + g0[1][2]) * (1.f / DM), m1 = (hi ? g1[0][3] + g1[1][3] : g1[0][2] + g1[1][2]) * (1.f / DM);
        const float q0 = (hi ? g0[0][1] + g0[1][1] : g0[0][0] + g0[1][0]) * (1.f / DM), q1 = (hi ? g1[0][1] + g1[1][1] : g1[0][0] + g1[1][0]) * (1.f / DM);
        ((float2*)(sm + SM_STATS))[w8 * 16 + (lane >> 2)] = make_float2(m0, rsqrtf(fmaxf(q0 - m0 * m0, 0.f) + 1e-5f));
        ((float2*)(sm + SM_STATS))[w8 * 16 + (lane >> 2) + 8] = make_float2(m1, rsqrtf(fmaxf(q1 - m1 * m1, 0.f) + 1e-5f));
    }
    __syncwarp();
    if (lane == 0) mbar_arrive(BAR(B_ST), 16);
}
__device__ __forceinline__ void first_layer_cols(uint32_t sb, char* sm, int w8, int lane) {
    float c[2][4] = {};
    float* cs = (float*)(sm + SM_CSQ) + (w8 & 3) * 16 + (lane >> 2);
#pragma unroll 1
    for (int kb = 0; kb < 7; kb++) {
        mbar_wait(FULL(Q1_SLOT(kb)), 0);
        colsum64(c, sb + Q1_SLOT(kb) * SLOT + (w8 >> 2) * 8192, w8 & 3, lane);
    }
    if ((lane & 3) == 0) {
        cs[(w8 >> 2) * 56] = c[0][0] + c[1][0];
        if ((w8 & 3) < 3) cs[(w8 >> 2) * 56 + 8] = c[0][2] + c[1][2];
    }
    if (w8 == 0 && lane < 28) ((float2*)(sm + SM_CSQ))[56 + lane] = make_float2(0.f, 0.f);
    __syncwarp();
    if (lane == 0) mbar_arrive(BAR(B_ST), 16);
#pragma unroll
    for (int i = 0; i < 4; i++) { c[0][i] = c[1][i] = 0.f; mbar_wait(FULL(Q1_SLOT(i)), 1); }
    nb_sync(NB_SKIP, 512);
#pragma unroll 1
    for (int i = 0; i < 4 - (w8 >> 2); i++) colsum64(c, sb + Q1_SLOT(i) * SLOT + (w8 >> 2) * 8192, w8 & 3, lane);
    if ((lane & 3) == 0) {
        atomicAdd(cs + 112, c[0][0] + c[1][0]);
        if ((w8 & 3) < 3) atomicAdd(cs + 120, c[0][2] + c[1][2]);
    }
    __syncwarp();
}

template <int N>
__device__ __forceinline__ void qkv_phase(uint32_t sb, char* sm, uint32_t pm, int l, int rb, int rh, int warp4, int lane, int ns) {
    constexpr bool P1 = N == 120;
    constexpr int NU = N / 56;
    const int q = lane & 3;
    float acc[N / 2];
    const uint64_t da0 = mkdesc(sb + rh * 8192, 16, 1024, 1), db0 = mkdesc(sb, 8192, 1024, 1);
    const uint32_t pe = (lane & 1) ? 0x1000000u : 0u;
    if (!P1) nb_sync(NB_ORD0, 512);
#pragma unroll
    for (int kb = -1; kb < 7; kb++) {
        if (P1 && kb == 1 && l == 0) mbar_wait(BAR(B_ST), 0);
        if (kb >= 0) {
            const uint64_t db = db0 + (P1 ? Q1_SLOT(kb) * 1024 : Q1_SLOT(kb >> 1) * 1024 + (kb & 1) * 512);
            wg_fence();
#pragma unroll
            for (int k = 0; k < 4; k++) {
                if (kb + k == 0) wgmma_qkvz<N>(acc, da0, db);
                else wgmma_qkv<N>(acc, da0 + kb * 1024 + k * 2, db + k * 128);
            }
            wg_commit();
        }
        if (kb < 6) {
            const int kn = kb + 1;
            if (P1) { mbar_wait(FULL(kn), (pm >> kn) & 1); mbar_wait(FULL(Q1_SLOT(kn)), (pm >> Q1_SLOT(kn)) & 1); }
            else if (!(kn & 1)) mbar_wait(FULL(Q1_SLOT(kn >> 1)), ((pm >> Q1_SLOT(kn >> 1)) ^ 1) & 1);
        }
        else if (P1 && l == 0) nb_arrive(NB_SKIP, 512);
        if (P1 && kb >= 1 && kb <= 4) {
            wg_wait<1>();
            if (lane < 2) mbar_arrive_c(EMPTY(Q1_SLOT(kb - 1)) ^ pe, 2);
        }
        if (!P1 && kb == 2) {
            wg_wait<1>();
            if (lane < 2) mbar_arrive_c(EMPTY(8) ^ pe, 2);
        }
    }
    if (P1) mbar_wait(BAR(B_ST), 0);
    else mbar_wait(EMPTY(8), ((pm >> 8) ^ 1) & 1);
    wg_wait<0>();
    fence_regs(acc);
    if (lane < 7) mbar_arrive(EMPTY(lane), 2);
    else if (lane >= 8 && lane < (P1 ? 10 : 14)) mbar_arrive_c(EMPTY(P1 ? 13 : 9 + ((lane - 8) >> 1)) ^ pe, 2);
    if (P1) nb_sync(NB_PAIR, 256);
    const int r = rh * 64 + warp4 * 16 + (lane >> 2);
    const float2 st0 = ((const float2*)(sm + SM_STATS))[r], st1 = ((const float2*)(sm + SM_STATS))[r + 8];
    const float* s_csq = (const float*)(sm + SM_CSQ);
    const int sr = rh * 64 + warp4 * 16 + (lane & 7) + ((lane >> 3) & 1) * 8;
    const uint32_t sa0 = sb + sr * 64 + (((lane >> 4) ^ ((sr >> 1) & 3)) << 4), sa1 = sa0 ^ 32;
    const int rank = rb & 1;
    const uint32_t own = P1 ? 12 * SLOT : 8 * SLOT + rank * 8192, oth = 7 * SLOT;
    const uint32_t ev = rank ? oth : own, od = rank ? own : oth;
#pragma unroll
    for (int u = 0; u < NU; u++) {
        const float sc = P1 ? 1.f : 0.18898223650461362f * 1.4426950408889634f;
        const float a0 = st0.y * sc, a1 = st1.y * sc;
        uint32_t pk[14];
#pragma unroll
        for (int j = 0; j < 7; j++) {
            const int jj = u * 8 + j;
            const float2 cs = *(const float2*)(s_csq + ((P1 ? u * 7 : 14) + j) * 8 + 2 * q);
            pk[2 * j] = packbf((acc[4 * jj] - st0.x * cs.x) * a0, (acc[4 * jj + 1] - st0.x * cs.y) * a0);
            pk[2 * j + 1] = packbf((acc[4 * jj + 2] - st1.x * cs.x) * a1, (acc[4 * jj + 3] - st1.x * cs.y) * a1);
        }
        const bool isk = P1 && u == 0;
        const uint32_t e0 = q < 2 ? pk[6] : 0u, e1 = q < 2 ? pk[7] : 0u, o0 = q < 2 ? 0u : pk[6], o1 = q < 2 ? 0u : pk[7];
        auto norms = [&]() {
            float g[4][4] = {};
            hmma(g[0], pk[0], pk[1], pk[2], pk[3], pk[0], pk[2]); hmma(g[1], pk[0], pk[1], pk[2], pk[3], pk[1], pk[3]);
            hmma(g[2], o0, o1, pk[8], pk[9], o0, pk[8]); hmma(g[3], o0, o1, pk[8], pk[9], o1, pk[9]);
            hmma(g[0], pk[4], pk[5], e0, e1, pk[4], e0); hmma(g[1], pk[4], pk[5], e0, e1, pk[5], e1);
            hmma(g[2], pk[10], pk[11], pk[12], pk[13], pk[10], pk[12]); hmma(g[3], pk[10], pk[11], pk[12], pk[13], pk[11], pk[13]);
#pragma unroll
            for (int o = 0; o < 2; o++) {
                const unsigned b = max(max(__float_as_uint(g[2 * o][0]) & 0x7FFFFFFFu, __float_as_uint(g[2 * o][1]) & 0x7FFFFFFFu),
                                       max(__float_as_uint(g[2 * o + 1][2]) & 0x7FFFFFFFu, __float_as_uint(g[2 * o + 1][3]) & 0x7FFFFFFFu));
                const unsigned mx = min(__reduce_max_sync(0xffffffffu, b), 0x7F800000u);
                if (P1) {
                    if (lane < 8) g_nrm[(((l * 16 + 2 * ns + o) * 16 + rb) * 8 + rh * 4 + warp4) * 8 + lane] = __uint_as_float(mx);
                } else if (lane == 0) {
                    if (o == rank) atomicMax((unsigned*)(sm + SM_QN + l * 4), mx);
                    else asm volatile("red.async.relaxed.cluster.shared::cluster.mbarrier::complete_tx::bytes.max.u32 [%0], %1, [%2];"
                                      ::"r"(PEER(sb + SM_QN + l * 4)), "r"(mx), "r"(PEER(FULL(13))) : "memory");
                }
            }
        };
        if (isk) norms();
        const uint32_t pm2 = POLY_MASK >> (2 * warp4), pc = P1 ? V_PAD_BITS : Q_PAD_BITS;
        uint32_t pd0 = (q & 1) ? 0u : (isk ? ((pm2 & 1) ? K_POLY_BITS : K_MUFU_BITS) : pc);
        uint32_t pd1 = (q & 1) ? 0u : (isk ? ((pm2 & 2) ? K_POLY_BITS : K_MUFU_BITS) : pc);
        if (q >= 2) { const uint32_t a = pk[6], b = pk[7]; pk[6] = pd0; pk[7] = pd1; pd0 = a; pd1 = b; }
        if (P1) {
            stsm4(sa0 + ev + u * 8192, pk[0], pk[1], pk[2], pk[3]);
            stsm4(sa1 + ev + u * 8192, pk[4], pk[5], pk[6], pk[7]);
            stsm4(sa0 + od + u * 8192, pd0, pd1, pk[8], pk[9]);
            stsm4(sa1 + od + u * 8192, pk[10], pk[11], pk[12], pk[13]);
        } else {
            if (rank) { stsm4(sa0 + own, pk[0], pk[1], pk[2], pk[3]); stsm4(sa1 + own, pk[4], pk[5], pk[6], pk[7]); }
            else { stsm4(sa0 + own, pd0, pd1, pk[8], pk[9]); stsm4(sa1 + own, pk[10], pk[11], pk[12], pk[13]); }
            __syncwarp();
#pragma unroll
            for (int i = 0; i < 2; i++) {
                const uint32_t o = sb + own + rh * 4096 + warp4 * 1024 + i * 512 + lane * 16;
                uint4 v;
                asm volatile("ld.shared.v4.b32 {%0,%1,%2,%3}, [%4];" : "=r"(v.x), "=r"(v.y), "=r"(v.z), "=r"(v.w) : "r"(o) : "memory");
                asm volatile("st.async.shared::cluster.mbarrier::complete_tx::bytes.v4.b32 [%0], {%1,%2,%3,%4}, [%5];"
                             ::"r"(PEER(o)), "r"(v.x), "r"(v.y), "r"(v.z), "r"(v.w), "r"(PEER(FULL(8))) : "memory");
            }
            __syncwarp();
            if (rank) { stsm4(sa0 + own, pd0, pd1, pk[8], pk[9]); stsm4(sa1 + own, pk[10], pk[11], pk[12], pk[13]); }
            else { stsm4(sa0 + own, pk[0], pk[1], pk[2], pk[3]); stsm4(sa1 + own, pk[4], pk[5], pk[6], pk[7]); }
            fence_async_smem();
            __syncwarp();
            if (lane == 0) mbar_arrive(BAR(B_LOC), 1);
            norms();
            __syncwarp();
        }
    }
    if (P1) {
        nb_arrive(NB_ORD0, 512);
        fence_async_smem();
        nb_arrive(NB_HST + rh, 160);
    }
}

__device__ __forceinline__ void proj_phase(const bool DOWN, uint32_t sb, const float2* s_stats, uint32_t pm, int wg, int warp4, int lane, __nv_bfloat16* dst,
                                           float2* stats_out) {
    const int NKB = DOWN ? 28 : 8;
    float acc[32];
    zero_regs(acc);
    const uint64_t da0 = mkdesc(sb + wg * 8192, 16, 1024, 1), db0 = mkdesc(sb, 8192, 1024, 1);
    uint32_t rel = 0;
    uint32_t as = 0, pa = DOWN ? pm ^ 0x200u : pm, bs = DOWN ? 10 : 9, pb = pm, a7 = DOWN ? 0 : 8;
    mbar_wait(FULL(0), pm & 1);
    if (DOWN) nb_sync(NB_ORD1, 512);
    mbar_wait(FULL(bs), (pm >> bs) & 1);
#pragma unroll 1
    for (int kp = 0; kp < NKB / 2; kp++) {
#pragma unroll
        for (int hf = 0; hf < 2; hf++) {
            wg_fence();
#pragma unroll
            for (int k = 0; k < 4; k++) wgmma_ss_64<1>(acc, da0 + as * 1024 + k * 2, db0 + bs * 1024 + hf * 512 + k * 128);
            wg_commit();
            uint32_t nrel = lane < 2 ? EMPTY(as) : ((hf == 1 && lane < 4) ? EMPTY(bs) : 0);
            if ((lane == 1 && as >= 7) || (hf == 1 && lane == 3)) nrel = PEER(nrel);
            as = as == 6 ? a7 : (as == 9 ? 0 : as + 1);
            if (as == 0) { pa = ~pa; a7 = 9; }
            if (hf == 0) {
                mbar_wait(FULL(as), (pa >> as) & 1);
            } else if (kp + 1 < NKB / 2) {
                if (DOWN) { if (bs == 8) { bs = 10; pb = ~pb; } else bs = bs == 12 ? 7 : bs + 1; } else bs = bs == 11 ? 7 : bs + 1;
                mbar_wait(FULL(as), (pa >> as) & 1);
                mbar_wait(FULL(bs), (pb >> bs) & 1);
            }
            wg_wait<1>();
            if (rel) mbar_arrive_c(rel, 2);
            rel = nrel;
        }
    }
    nb_arrive(NB_SKIP, 512);
    mbar_wait(BAR(B_RES), DOWN ? 1 : 0);
    const int r = warp4 * 16 + (lane & 7) + ((lane >> 3) & 1) * 8, cs = lane >> 4;
    const uint32_t base = sb + SM_STG + wg * 8192 + r * 128;
    const float f0 = DOWN ? 0.5f * s_stats[wg * 64 + warp4 * 16 + (lane >> 2)].y : 1.f, f1 = DOWN ? 0.5f * s_stats[wg * 64 + warp4 * 16 + (lane >> 2) + 8].y : 1.f;
    uint32_t pk[16];
#pragma unroll
    for (int j = 0; j < 8; j += 2) ldsm4(base + (((j + cs) ^ (r & 7)) << 4), pk[2 * j], pk[2 * j + 1], pk[2 * j + 2], pk[2 * j + 3]);
    wg_wait<0>();
    fence_regs(acc);
    if (rel) mbar_arrive_c(rel, 2);
#pragma unroll
    for (int j = 0; j < 8; j++) {
        pk[2 * j] = packbf(fmaf(acc[4 * j], f0, bflo(pk[2 * j])), fmaf(acc[4 * j + 1], f0, bfhi(pk[2 * j])));
        pk[2 * j + 1] = packbf(fmaf(acc[4 * j + 2], f1, bflo(pk[2 * j + 1])), fmaf(acc[4 * j + 3], f1, bfhi(pk[2 * j + 1])));
    }
#pragma unroll
    for (int j = 0; j < 8; j += 2) stsm4(base + (((j + cs) ^ (r & 7)) << 4), pk[2 * j], pk[2 * j + 1], pk[2 * j + 2], pk[2 * j + 3]);
    __syncwarp();
    {
        uint4 v[4];
#pragma unroll
        for (int i = 0; i < 4; i++) {
            const int rr = warp4 * 16 + i * 4 + (lane >> 3);
            asm volatile("ld.shared.v4.b32 {%0,%1,%2,%3}, [%4];" : "=r"(v[i].x), "=r"(v[i].y), "=r"(v[i].z), "=r"(v[i].w)
                         : "r"(sb + SM_STG + wg * 8192 + rr * 128 + (((lane & 7) ^ (rr & 7)) << 4)) : "memory");
        }
#pragma unroll
        for (int i = 0; i < 4; i++) stg128(dst + (size_t)(wg * 64 + warp4 * 16 + i * 4 + (lane >> 3)) * DM + (lane & 7) * 8, v[i]);
    }
    nb_arrive(NB_REL, 288);
    if (stats_out) {
        const int rl = wg * 64 + warp4 * 16 + (lane >> 2);
        float s0 = 0.f, s1 = 0.f;
#pragma unroll
        for (int j = 0; j < 8; j++) { s0 += bflo(pk[2 * j]) + bfhi(pk[2 * j]); s1 += bflo(pk[2 * j + 1]) + bfhi(pk[2 * j + 1]); }
        s0 += __shfl_xor_sync(0xffffffffu, s0, 1); s1 += __shfl_xor_sync(0xffffffffu, s1, 1);
        s0 += __shfl_xor_sync(0xffffffffu, s0, 2); s1 += __shfl_xor_sync(0xffffffffu, s1, 2);
        s0 *= 1.f / 64.f; s1 *= 1.f / 64.f;
        float m0 = 0.f, m1 = 0.f;
#pragma unroll
        for (int j = 0; j < 8; j++) {
            float a = bflo(pk[2 * j]) - s0, b = bfhi(pk[2 * j]) - s0, c = bflo(pk[2 * j + 1]) - s1, d = bfhi(pk[2 * j + 1]) - s1;
            m0 += a * a + b * b; m1 += c * c + d * d;
        }
        m0 += __shfl_xor_sync(0xffffffffu, m0, 1); m1 += __shfl_xor_sync(0xffffffffu, m1, 1);
        m0 += __shfl_xor_sync(0xffffffffu, m0, 2); m1 += __shfl_xor_sync(0xffffffffu, m1, 2);
        if ((lane & 3) == 0) { stats_out[rl] = make_float2(s0, m0); stats_out[rl + 8] = make_float2(s1, m1); }
        nb_arrive(NB_REL + 1, 288);
    }
}
__device__ __forceinline__ void proj_idle(const bool DOWN, uint32_t sb, int wi, int lane, int flag_idx) {
    nb_sync(NB_SKIP, 512);
    if (wi == 8) {
        nb_sync(NB_REL, 288);
        if (lane == 0) { if (flag_idx >= 0) flag_release(flag_idx); mbar_arrive(BAR(B_FR), 1); }
        if (DOWN && lane < 2) mbar_arrive_c(EMPTY(13) ^ (lane ? 0x1000000u : 0u), 16);
        __syncwarp();
    } else if (wi == 12 && flag_idx >= 0) {
        nb_sync(NB_REL + 1, 288);
        if (lane == 0) flag_release(flag_idx + FL_XS_OFF);
        __syncwarp();
    }
}

#define PHASE_VARS                                                                                          \
    int tid, vid = vid_in;                                                                                  \
    asm volatile("mov.u32 %0, %%tid.x;" : "=r"(tid));                                                       \
    asm volatile("" : "+r"(vid));                                                                           \
    const int wi = __shfl_sync(0xffffffffu, tid >> 5, 0), wg = wi >> 2, warp4 = wi & 3, lane = tid & 31, q = lane & 3; \
    const int g = vid >> 4, ns = vid & 7, rb = vid >> 3;                                                    \
    const bool act = ns < 7, issuer = (tid & 127) == 0;                                                     \
    (void)wg; (void)warp4; (void)q; (void)ns; (void)rb; (void)g; (void)act; (void)issuer;

__device__ __forceinline__ void consumer(const Params& P, uint32_t sb, char* sm, const int vid_in) {
    uint32_t pm = 0;
    const float2* s_stats = (const float2*)(sm + SM_STATS);

#pragma unroll 1
    for (int step = 0; step < 4; step++) {
        const int l = step >> 1;
        if (step & 1) {
        {
            PHASE_VARS
            const int pr = wg >> 1, rh = wg & 1;
#pragma unroll 1
            for (int t = pr; t < 4; t += 2) {
                const bool work = t < 3 || rh == (ns & 1);
                const bool lastA = t == 2 || t == 3 || (t == 1 && rh != (ns & 1));
                float acc[64];
                const int ch = t < 3 ? 8 * t + ns : 24 + (ns >> 1);
                const uint32_t cnt = lane < 2 ? (t < 3 ? 2 : 4) : 1;
                const uint32_t rbase = lane == 1 ? PEER(EMPTY(0)) : EMPTY(0);
                const bool relon = lane < 2 || (lane < 4 && lastA);
                if (t > 0) nb_sync(pr ? NB_ORD0 : NB_ORD1, 512);
                if (work) {
                    const uint64_t da0 = mkdesc(sb + rh * 8192, 16, 1024, 1), db0 = mkdesc(sb, 8192, 1024, 1);
                    uint32_t c = t, pb = (t & 1) ? ~pm : pm;
                    uint32_t bs = c < 1 ? 12 : 6 + c, pbs = 0;
                    if (t == 0) mbar_wait(FULL(0), pm & 1);
                    mbar_wait(FULL(bs), (pb >> bs) & 1);
                    wg_fence();
                    wgmma_ssz_128<1>(acc, da0, db0 + bs * 1024);
#pragma unroll
                    for (int k = 1; k < 4; k++) wgmma_ss_128<1>(acc, da0 + k * 2, db0 + bs * 1024 + k * 128);
                    wg_commit();
#pragma unroll 1
                    for (int kb = 1; kb < 7; kb++) {
                        const uint32_t obs = pbs;
                        pbs = bs;
                        if (++c == 6) { c = 0; pb = ~pb; }
                        bs = c < 1 ? 12 : 6 + c;
                        if (t == 0) mbar_wait(FULL(kb), (pm >> kb) & 1);
                        mbar_wait(FULL(bs), (pb >> bs) & 1);
                        if (kb == 6) nb_arrive(pr ? NB_ORD1 : NB_ORD0, 512);
                        wg_wait<1>();
                        if (relon && kb > 1) mbar_arrive_c(rbase + (lane < 2 ? obs : kb - 2) * 8, cnt);
                        wg_fence();
#pragma unroll
                        for (int k = 0; k < 4; k++) wgmma_ss_128<1>(acc, da0 + kb * 1024 + k * 2, db0 + bs * 1024 + k * 128);
                        wg_commit();
                    }
                    wg_wait<1>();
                    if (relon) mbar_arrive_c(rbase + (lane < 2 ? pbs : 5) * 8, cnt);
                    if (t > 0) mbar_wait(t < 2 ? BAR(B_ST) : BAR(B_STG + pr * 4 + 3), t < 2 ? 1 : l);
                    wg_wait<0>();
                    fence_regs(acc);
                    if (relon && !(t == 3 && lane < 2)) mbar_arrive_c(rbase + (lane < 2 ? bs : 6) * 8, cnt);
                    if (t == 0) mbar_wait(BAR(B_ST), 1);
                    {
                        PHASE_VARS
                        const int r = rh * 64 + warp4 * 16 + (lane >> 2);
                        const float2 st0 = s_stats[r], st1 = s_stats[r + 8];
                        const float g0 = 0.5f * st0.y, g1 = 0.5f * st1.y;
                        const float4* cg = (const float4*)(sm + SM_CSG) + pr * 32 + q;
                        const int sr = warp4 * 16 + (lane & 7) + ((lane >> 3) & 1) * 8, cs = lane >> 4;
                        const uint32_t stg = sb + (t < 3 ? SM_STG + rh * 8192 : 9 * SLOT), base = stg + sr * 128;
                        uint32_t pk[16];
#pragma unroll
                        for (int j = 0; j < 8; j++) {
                            const float4 c = cg[j * 4];
                            float h0 = acc[32 + 4 * j] - st0.x * c.z; h0 = fmaf(h0, tanh_approx((acc[4 * j] - st0.x * c.x) * g0), h0);
                            float h1 = acc[32 + 4 * j + 1] - st0.x * c.w; h1 = fmaf(h1, tanh_approx((acc[4 * j + 1] - st0.x * c.y) * g0), h1);
                            float h2 = acc[32 + 4 * j + 2] - st1.x * c.z; h2 = fmaf(h2, tanh_approx((acc[4 * j + 2] - st1.x * c.x) * g1), h2);
                            float h3 = acc[32 + 4 * j + 3] - st1.x * c.w; h3 = fmaf(h3, tanh_approx((acc[4 * j + 3] - st1.x * c.y) * g1), h3);
                            pk[2 * j] = packbf(h0, h1); pk[2 * j + 1] = packbf(h2, h3);
                        }
                        if (t == 3) nb_sync(NB_WG + wg, 128);
                        else if (t > 0) mbar_wait(BAR(B_STG + rh * 4 + t - 1), l);
#pragma unroll
                        for (int j = 0; j < 8; j += 2) stsm4(base + (((j + cs) ^ (sr & 7)) << 4), pk[2 * j], pk[2 * j + 1], pk[2 * j + 2], pk[2 * j + 3]);
                        fence_async_smem();
                        if (t < 3) {
                            nb_arrive(NB_HST + rh, 160);
                        } else if (warp4 == 1) {
                            nb_sync(NB_WG + wg, 128);
                            if (lane == 0) {
                                tma_st2(&P.h_st, ch * 64, l * SEQ + rb * 128 + rh * 64, stg);
                                bulk_commit(); bulk_wait_read();
                                mbar_arrive(EMPTY(9), 16); mbar_arrive_c(PEER(EMPTY(9)), 16);
                                bulk_wait_all();
                                flag_release(FL_H(l, rb, 3));
                            }
                            __syncwarp();
                        } else {
                            nb_arrive(NB_WG + wg, 128);
                        }

                    }
                } else {
                    nb_arrive(NB_ORD1, 512);
                }
            }
            if (pr == 0 && !act) nb_sync(NB_ORD1, 512);
            pm ^= PM_GU;
        }

        } else {
        {
            PHASE_VARS
            if (wg >= 2) {
                if (l == 0) first_layer_cols(sb, sm, wi - 8, lane);
                qkv_phase<56>(sb, sm, pm, l, rb, wg - 2, warp4, lane, ns);
            } else {
                if (l == 0) first_layer_rows(sb, sm, wi, lane);
                qkv_phase<120>(sb, sm, pm, l, rb, wg, warp4, lane, ns);
            }
            pm ^= PM_QKV;
        }

        {
            const bool lane0 = (threadIdx.x & 31) == 0;
            mbar_wait(BAR(B_LOC), l);
            if ((__shfl_sync(0xffffffffu, threadIdx.x >> 8, 0) ^ (vid_in >> 3)) & 1) {
                mbar_wait(FULL(8), (pm >> 8) & 1);
                fence_async_smem();
            }
            const uint64_t qd = mkdesc(sb + 8 * SLOT + __shfl_sync(0xffffffffu, threadIdx.x >> 7, 0) * 4096, 16, 512, 2);
            uint32_t cneg1 = 0xBF80BF80u;
            asm volatile("" : "+r"(cneg1));
            float o[16];
            zero_regs(o);
            const uint64_t kd0 = mkdesc(sb, 16, 512, 2), vd0 = mkdesc(sb + 8192, 512, 512, 2);
            {
                float s[32];
                uint32_t p0[16], p1[16];
                wg_fence();
                wgmma_ssz_64<0>(s, qd, kd0 + 12 * 1024);
                wgmma_ss_64<0>(s, qd + 2, kd0 + 12 * 1024 + 2);
                wg_commit();
                wg_wait<0>(); fence_regs(s);
                softmax_fast(s, p0, cneg1);
#pragma unroll 1
                for (int j = 0; j < 16; j++) {
                    const uint32_t cur = j < 2 ? 12 + j : (j - 2) & 3, nxt = j < 1 ? 13 : (j - 1) & 3;
                    const uint64_t kd = kd0 + cur * 1024, vd = vd0 + cur * 1024;
                    wg_fence();
                    wgmma_ssz_64<0>(s, qd, kd + 256);
                    wgmma_ss_64<0>(s, qd + 2, kd + 258);
                    wg_commit();
#pragma unroll
                    for (int k = 0; k < 4; k++) wgmma_rs_32<1>(o, p0[4 * k], p0[4 * k + 1], p0[4 * k + 2], p0[4 * k + 3], vd + k * 64);
                    wg_commit();
                    wg_wait<1>(); fence_regs(s);
                    softmax_fast(s, p1, cneg1);
                    wg_wait<0>(); fence_regs(o); fence_regs(p0);
                    if (j == 15) break;
                    mbar_wait(FULL(nxt), ((pm >> nxt) ^ (j < 1 ? 0 : (j - 1) >> 2)) & 1);
                    const uint64_t kn = kd0 + nxt * 1024;
                    wg_fence();
                    wgmma_ssz_64<0>(s, qd, kn);
                    wgmma_ss_64<0>(s, qd + 2, kn + 2);
                    wg_commit();
#pragma unroll
                    for (int k = 0; k < 4; k++) wgmma_rs_32<1>(o, p1[4 * k], p1[4 * k + 1], p1[4 * k + 2], p1[4 * k + 3], vd + 256 + k * 64);
                    wg_commit();
                    wg_wait<1>(); fence_regs(s);
                    softmax_fast(s, p0, cneg1);
                    wg_wait<0>(); fence_regs(o); fence_regs(p1);
                    if (lane0 && j >= 2) mbar_arrive(EMPTY(cur), 2);
                }
                wg_fence();
#pragma unroll
                for (int k = 0; k < 4; k++) wgmma_rs_32<1>(o, p1[4 * k], p1[4 * k + 1], p1[4 * k + 2], p1[4 * k + 3], vd0 + 1 * 1024 + 256 + k * 64);
                wg_commit(); wg_wait<0>(); fence_regs(o);
                if (lane0) mbar_arrive(EMPTY(1), 2);
            }
            PHASE_VARS
            if (__shfl_sync(0xffffffffu, *(volatile int*)(sm + SM_DEC), 0)) {
                uint32_t qf[8];
                {
                    const int r = warp4 * 16 + (lane & 7) + ((lane >> 3) & 1) * 8, cs = lane >> 4;
                    const uint32_t base = sb + 8 * SLOT + wg * 4096 + r * 64;
                    ldsm4(base + (((0 + cs) ^ ((r >> 1) & 3)) << 4), qf[0], qf[1], qf[2], qf[3]);
                    ldsm4(base + (((2 + cs) ^ ((r >> 1) & 3)) << 4), qf[4], qf[5], qf[6], qf[7]);
                }
                if (rb & 1) { if (q == 0) { qf[0] = 0; qf[1] = 0; } }
                else if (q == 2) { qf[6] = 0; qf[7] = 0; }
#pragma unroll
                for (int i = 0; i < 16; i++) o[i] = 0.f;
                float m0 = -INFINITY, m1 = -INFINITY;
#pragma unroll 1
                for (int j = 0; j < 32; j++) {
                    float s[32];
                    uint32_t p[16];
                    const uint32_t cur = ((j >> 1) + 14) & 3;
                    if (!(j & 1)) mbar_wait(FULL(cur), ((pm >> cur) ^ (((j >> 1) + 14) >> 2)) & 1);
                    const uint64_t kd = kd0 + cur * 1024 + (j & 1) * 256, vd = vd0 + cur * 1024 + (j & 1) * 256;
                    wg_fence();
                    wgmma_rsz_64<0>(s, qf[0], qf[1], qf[2], qf[3], kd);
                    wgmma_rs_64<0>(s, qf[4], qf[5], qf[6], qf[7], kd + 2);
                    wg_commit(); wg_wait<0>(); fence_regs(s);
                    float n0 = m0, n1 = m1;
#pragma unroll
                    for (int i = 0; i < 8; i++) { n0 = fmaxf(n0, fmaxf(s[4 * i], s[4 * i + 1])); n1 = fmaxf(n1, fmaxf(s[4 * i + 2], s[4 * i + 3])); }
                    n0 = fmaxf(n0, __shfl_xor_sync(0xffffffffu, n0, 1)); n1 = fmaxf(n1, __shfl_xor_sync(0xffffffffu, n1, 1));
                    n0 = fmaxf(n0, __shfl_xor_sync(0xffffffffu, n0, 2)); n1 = fmaxf(n1, __shfl_xor_sync(0xffffffffu, n1, 2));
                    const float c0 = ex2(m0 - n0), c1 = ex2(m1 - n1);
                    m0 = n0; m1 = n1;
#pragma unroll
                    for (int i = 0; i < 4; i++) { o[4 * i] *= c0; o[4 * i + 1] *= c0; o[4 * i + 2] *= c1; o[4 * i + 3] *= c1; }
#pragma unroll
                    for (int i = 0; i < 8; i++) {
                        p[2 * i] = packbf(ex2(s[4 * i] - m0), ex2(s[4 * i + 1] - m0));
                        p[2 * i + 1] = packbf(ex2(s[4 * i + 2] - m1), ex2(s[4 * i + 3] - m1));
                    }
                    fence_regs(o);
                    wg_fence();
#pragma unroll
                    for (int k = 0; k < 4; k++) wgmma_rs_32<1>(o, p[4 * k], p[4 * k + 1], p[4 * k + 2], p[4 * k + 3], vd + k * 64);
                    wg_commit(); wg_wait<0>(); fence_regs(o);
                    if ((j & 1) && lane == 0) mbar_arrive(EMPTY(cur), 2);
                }
            }
            pm ^= PM_ATT;
            if (wg == 0) nb_arrive(NB_PARK, 224);
            nb_sync(NB_WG + wg, 128);
            const bool odd = rb & 1;
            const int sl = (lane & ~3) | (odd ? 0 : 2);
            const float i0 = rcp(__shfl_sync(0xffffffffu, odd ? o[0] : o[12], sl)), i1 = rcp(__shfl_sync(0xffffffffu, odd ? o[2] : o[14], sl));
            {
                const int r = warp4 * 16 + (lane & 7) + ((lane >> 3) & 1) * 8, cs = lane >> 4;
                const uint32_t base = sb + 8 * SLOT + wg * 4096 + r * 64;
                const bool z0 = odd && q < 2, z3 = !odd && q >= 2;
                stsm4(base + (((0 + cs) ^ ((r >> 1) & 3)) << 4), z0 ? 0u : packbf(o[0] * i0, o[1] * i0), z0 ? 0u : packbf(o[2] * i1, o[3] * i1),
                      packbf(o[4] * i0, o[5] * i0), packbf(o[6] * i1, o[7] * i1));
                stsm4(base + (((2 + cs) ^ ((r >> 1) & 3)) << 4), packbf(o[8] * i0, o[9] * i0), packbf(o[10] * i1, o[11] * i1),
                      z3 ? 0u : packbf(o[12] * i0, o[13] * i0), z3 ? 0u : packbf(o[14] * i1, o[15] * i1));
            }
            __syncwarp();
#pragma unroll
            for (int i = 0; i < 2; i++) {
                const int rr = warp4 * 16 + i * 8 + (lane >> 2);
                uint4 v;
                asm volatile("ld.shared.v4.b32 {%0,%1,%2,%3}, [%4];" : "=r"(v.x), "=r"(v.y), "=r"(v.z), "=r"(v.w)
                             : "r"(sb + 8 * SLOT + wg * 4096 + rr * 64 + ((q ^ ((rr >> 1) & 3)) << 4)) : "memory");
                stg128(g_o + (size_t)(l * SEQ + g * 256 + wg * 64 + rr) * 512 + (2 * ns + (rb & 1)) * 32 + q * 8, v);
            }
            if (warp4 == 0) {
                nb_sync(NB_WG + wg, 128);
                if (lane < 2) mbar_arrive_c(EMPTY(8) ^ (lane ? 0x1000000u : 0u), 4);
                if (lane == 0) flag_release(FL_O(l, 2 * g + (wg >> 1)));
                __syncwarp();
            } else {
                nb_arrive(NB_WG + wg, 128);
            }
        }

        }
        {
            PHASE_VARS
            const bool down = step & 1;
            if (act) {
                if (wg < 2) proj_phase(down, sb, s_stats, pm, wg, warp4, lane, (step < 3 ? g_x + (size_t)step * SEQ * DM : P.out) + (size_t)rb * 128 * DM + ns * 64,
                                       step < 3 ? &g_st[((step * 16 + rb) * 7 + ns) * 128] : nullptr);
                else proj_idle(down, sb, wi, lane, step < 3 ? FL_X(step, rb) : -1);
                pm ^= down ? PM_DN : PM_WO;
            }
        }
    }
}

__device__ __forceinline__ int vid_from_bid(unsigned b) {
    unsigned g, p;
    const unsigned c = b >> 1;
    if (c < 4) { g = 0; p = 4 + c; }
    else if (c < 36) { g = (c - 4) & 7; p = (c - 4) >> 3; }
    else if (c < 64) { g = 1 + (c - 36) % 7; p = 4 + (c - 36) / 7; }
    else return b;
    return g * 16 + (b & 1) * 8 + p;
}

__global__ void __cluster_dims__(2, 1, 1) __launch_bounds__(NTHREADS, 1) fused_layers_kernel(const __grid_constant__ Params P) {
    extern __shared__ __align__(1024) char sm[];
    const uint32_t sb = s2u(sm);
    const int vid = vid_from_bid(blockIdx.x);
    const int warp = __shfl_sync(0xffffffffu, threadIdx.x >> 5, 0);
    if (warp >= 3) asm volatile("barrier.cluster.arrive.relaxed.aligned;" ::: "memory");
    if (warp >= 16) {
        asm volatile("setmaxnreg.dec.sync.aligned.u32 32;");
        if (warp >= 18 && vid < 128 && elect()) {
            if (warp == 18) {
                asm volatile("cp.async.bulk.prefetch.L2.global [%0], %1;" ::"l"((const char*)P.p_wqkv + vid * 9408), "r"(9408));
            } else {
#pragma unroll
                for (int i = 0; i < 10; i++) asm volatile("prefetch.tensormap [%0];" ::"l"(&P.x_in + (i * 5 + i / 2) % 10) : "memory");
            }
        }
        const unsigned ep = *(volatile unsigned*)&g_epoch + 1;
        asm volatile("barrier.cluster.wait.aligned;" ::: "memory");
        if (vid < 128) {
            if (warp == 16) producer_a(P, sb, sm, vid, ep);
            else if (warp == 17) producer_w(P, sb, vid);
            else service_warps(P, sb, sm, vid, ep, warp - 18);
            if (threadIdx.x == 576 && atomicAdd(&g_done, 1) + 1 == ep * 128) *(volatile unsigned*)&g_epoch = ep;
        }
    } else {
        if (threadIdx.x < 96 && (threadIdx.x & 31) == 0) {
#pragma unroll
            for (int i = 0; i < NSLOT; i++)
                if (i < 13 || warp < 2) mbar_init(BAR(warp * NSLOT + i), warp == 1 ? 32 : ((warp == 2 && i == 0) ? 256 : ((warp == 2 && i == B_LOC - B_ST) ? 10 : 1)));
            asm volatile("fence.mbarrier_init.release.cluster;" ::: "memory");
            fence_async_smem();
        }
        __syncwarp();
        if (warp < 3) asm volatile("barrier.cluster.arrive.relaxed.aligned;" ::: "memory");
        if (warp == 0 && vid < 128) {
            if (elect()) {
#pragma unroll
                for (int k = 0; k < 7; k++) { mbar_expect(FULL(k), SLOT); FIRE(k, &P.x_in, k * 64, (vid >> 3) * 128) }
            }
            __syncwarp();
        }
        if (threadIdx.x == 256) {
            uint32_t pa;
            asm volatile("mapa.shared::cluster.u32 %0, %1, %2;" : "=r"(pa) : "r"(sb), "r"((blockIdx.x & 1) ^ 1));
            if ((sb & 1023) || pa != PEER(sb)) __trap();
            *(uint2*)(sm + SM_QN) = make_uint2(0, 0);
        }
        asm volatile("barrier.cluster.wait.aligned;" ::: "memory");
        if (warp == 4 && vid < 128) {
            if (elect()) {
#pragma unroll
                for (int k = 0; k < 7; k++) {
                    mbar_expect(FULL(Q1_SLOT(k)), SLOT);
                    tma_mc2(sb + Q1_SLOT(k) * SLOT + ((vid >> 3) & 1) * 8192, &P.wqkv64, (((vid >> 3) & 1) + 1) * DM + (vid & 7) * 56, k * 64, FULL(Q1_SLOT(k)));
                }
            }
            __syncwarp();
        }
        asm volatile("setmaxnreg.inc.sync.aligned.u32 112;");
        if (vid >= 128) helper_cta(P, vid - 128, sm);
        else consumer(P, sb, sm, vid);
        __syncwarp();
        asm volatile("barrier.cluster.arrive.relaxed.aligned;\nbarrier.cluster.wait.aligned;" ::: "memory");
    }
}

typedef CUresult (*EncodeFn)(CUtensorMap*, CUtensorMapDataType, cuuint32_t, void*, const cuuint64_t*, const cuuint64_t*, const cuuint32_t*,
                             const cuuint32_t*, CUtensorMapInterleave, CUtensorMapSwizzle, CUtensorMapL2promotion, CUtensorMapFloatOOBfill);

static void enc2(EncodeFn f, CUtensorMap* m, const void* p, int cols, int rows, int bc, int br, CUtensorMapSwizzle sw) {
    cuuint64_t gd[2] = {(cuuint64_t)cols, (cuuint64_t)rows}, gs[1] = {(cuuint64_t)cols * 2};
    cuuint32_t bd[2] = {(cuuint32_t)bc, (cuuint32_t)br}, es[2] = {1, 1};
    f(m, CU_TENSOR_MAP_DATA_TYPE_BFLOAT16, 2, (void*)p, gd, gs, bd, es, CU_TENSOR_MAP_INTERLEAVE_NONE, sw, CU_TENSOR_MAP_L2_PROMOTION_L2_128B,
      CU_TENSOR_MAP_FLOAT_OOB_FILL_NONE);
}

extern "C" void kernel_launch(void* const* d_in, const int* in_sizes, int n_in, void* d_out, int out_size) {
    (void)in_sizes; (void)n_in; (void)out_size;
    static EncodeFn enc = nullptr;
    if (!enc) {
        void* fn = nullptr;
        cudaDriverEntryPointQueryResult qr;
        cudaGetDriverEntryPoint("cuTensorMapEncodeTiled", &fn, cudaEnableDefault, &qr);
        enc = (EncodeFn)fn;
        cudaFuncSetAttribute(fused_layers_kernel, cudaFuncAttributeMaxDynamicSharedMemorySize, SM_TOTAL);
    }
    void *px, *ph, *po;
    cudaGetSymbolAddress(&px, g_x); cudaGetSymbolAddress(&ph, g_h); cudaGetSymbolAddress(&po, g_o);
    Params P;
    const auto S128 = CU_TENSOR_MAP_SWIZZLE_128B;
    enc2(enc, &P.x_in, d_in[0], DM, SEQ, 64, 128, S128);
    enc2(enc, &P.x_ld, px, DM, 3 * SEQ, 64, 128, S128);
    enc2(enc, &P.h_ld, ph, FF, 2 * SEQ, 64, 128, S128);
    enc2(enc, &P.h_st, ph, FF, 2 * SEQ, 64, 64, S128);
    enc2(enc, &P.o_ld, po, 512, 2 * SEQ, 64, 128, S128);
    enc2(enc, &P.wqkv64, d_in[1], 1344, DM, 64, 64, S128);
    {
        cuuint64_t gd[4] = {DM, 32, 2, 8}, gs[3] = {DM * 2, 24 * DM * 2, 56 * DM * 2};
        cuuint32_t bd[4] = {64, 32, 2, 1}, es[4] = {1, 1, 1, 1};
        enc(&P.wo, CU_TENSOR_MAP_DATA_TYPE_BFLOAT16, 4, d_in[2], gd, gs, bd, es, CU_TENSOR_MAP_INTERLEAVE_NONE, S128,
            CU_TENSOR_MAP_L2_PROMOTION_L2_128B, CU_TENSOR_MAP_FLOAT_OOB_FILL_NONE);
    }
    enc2(enc, &P.wg, d_in[4], FF, DM, 64, 64, S128);
    enc2(enc, &P.wu, d_in[5], FF, DM, 64, 64, S128);
    enc2(enc, &P.wd, d_in[6], DM, FF, 64, 64, S128);
    P.out = (__nv_bfloat16*)d_out;
    P.p_wqkv = (const __nv_bfloat16*)d_in[1];
    P.p_wo = (const __nv_bfloat16*)d_in[2];
    P.p_wg = (const __nv_bfloat16*)d_in[4];
    P.p_wu = (const __nv_bfloat16*)d_in[5];
    P.p_wd = (const __nv_bfloat16*)d_in[6];
    fused_layers_kernel<<<NCTA, NTHREADS, SM_TOTAL>>>(P);
}
```
